```python
import torch

def _softmax(x, axis=-1):
    return torch.softmax(x, dim=axis)
def _gelu(x):
    return torch.nn.functional.gelu(x, approximate="tanh")
def _silu(x):
    return torch.nn.functional.silu(x)
def _sigmoid(x):
    return torch.sigmoid(x)
def _layernorm(x, axis=-1, eps=1e-5):
    m = x.mean(dim=axis, keepdim=True)
    v = x.var(dim=axis, keepdim=True, unbiased=False)
    return (x - m) / torch.sqrt(v + eps)
def _scatter_add(tgt, idx, src, axis=0):
    return tgt.clone().index_add_(axis, idx, src)
def _segment_sum(src, seg, n):
    out = torch.zeros((n,) + src.shape[1:], dtype=src.dtype)
    return out.index_add_(0, seg, src)
def _pad(x, pw):
    flat = tuple(v for pair in reversed(pw) for v in pair)
    return torch.nn.functional.pad(x, flat)

kernel_name = 'recurrent_scan__softmax_full_mha__geglu_ffn__prompt'

def setup_inputs():

    _w = (lambda a: (lambda t: t.to(torch.bfloat16) if t.is_floating_point() else t)(torch.as_tensor(a)))
    def _A_setup():
        B, S, D = 1, 2048, 1024
        return {
            "x": _w((lambda *s: torch.randn(*s, dtype=torch.bfloat16) * 0.05)(B, S, D)),
            "wqkv": _w((lambda *s: torch.randn(*s, dtype=torch.bfloat16) * 0.05)(D, 3 * D)),
            "wo": _w((lambda *s: torch.randn(*s, dtype=torch.bfloat16) * 0.05)(D, D)),
        }
    _A_in = _A_setup()

    def _B_setup():
        B, S, D, F = 1, 2048, 1024, 3584
        return {
            "x": _w((lambda *s: torch.randn(*s, dtype=torch.bfloat16) * 0.05)(B, S, D)),
            "w_gate": _w((lambda *s: torch.randn(*s, dtype=torch.bfloat16) * 0.05)(D, F)),
            "w_up": _w((lambda *s: torch.randn(*s, dtype=torch.bfloat16) * 0.05)(D, F)),
            "w_down": _w((lambda *s: torch.randn(*s, dtype=torch.bfloat16) * 0.05)(F, D)),
        }
    _B_in = _B_setup()

    return {
        "A_x": _A_in["x"],
        "A_wqkv": _A_in["wqkv"],
        "A_wo": _A_in["wo"],
        "B_x": _B_in["x"],
        "B_w_gate": _B_in["w_gate"],
        "B_w_up": _B_in["w_up"],
        "B_w_down": _B_in["w_down"],
    }

def reference(A_x, A_wqkv, A_wo, B_x, B_w_gate, B_w_up, B_w_down):
    def _A_ref(x, wqkv, wo):
        B, S, D = x.shape
        H = 32; Dh = D // H
        qkv = (lambda x, *d: x.permute(*d))((x @ wqkv).reshape(B, S, 3, H, Dh), 2, 0, 3, 1, 4)
        q, k, v = qkv[0], qkv[1], qkv[2]
        scale = Dh ** -0.5
        scores = torch.einsum("bhqd,bhkd->bhqk", q, k) * scale
        p = _softmax(scores, axis=-1)
        o = torch.einsum("bhqk,bhkd->bhqd", p, v)
        return (lambda x, *d: x.permute(*d))(o, 0, 2, 1, 3).reshape(B, S, D) @ wo

    def _B_ref(x, w_gate, w_up, w_down):
        return (_gelu(x @ w_gate) * (x @ w_up)) @ w_down

    x = A_x
    xn = _layernorm(x, axis=-1)
    s = _A_ref(xn, A_wqkv, A_wo)
    g = _silu(_B_ref(xn, B_w_gate, B_w_up, B_w_down))
    return x + s * g
```

```cpp
#include <cuda_runtime.h>
#include <cuda_bf16.h>
#include <cuda.h>
#include <stdint.h>

namespace {

typedef __nv_bfloat16 bf16;

constexpr int SEQ = 2048;
constexpr int DM = 1024;
constexpr int FF = 3584;
constexpr int NH = 32;
constexpr int DH = 32;

__device__ bf16 g_xn[SEQ * DM];
__device__ bf16 g_qkv[SEQ * 3 * DM];
__device__ bf16 g_h[SEQ * FF];
__device__ bf16 g_o[SEQ * DM];

__device__ __forceinline__ uint32_t smem_u32(const void* p) { return (uint32_t)__cvta_generic_to_shared(p); }

__device__ __forceinline__ void mbar_init(uint32_t bar, uint32_t count) {
  asm volatile("mbarrier.init.shared::cta.b64 [%0], %1;" ::"r"(bar), "r"(count) : "memory");
}
__device__ __forceinline__ void mbar_expect_tx(uint32_t bar, uint32_t bytes) {
  asm volatile("mbarrier.arrive.expect_tx.shared::cta.b64 _, [%0], %1;" ::"r"(bar), "r"(bytes) : "memory");
}
__device__ __forceinline__ void mbar_arrive(uint32_t bar) {
  asm volatile("mbarrier.arrive.shared::cta.b64 _, [%0];" ::"r"(bar) : "memory");
}
__device__ __forceinline__ void mbar_arrive_cluster(uint32_t bar, uint32_t cta) {
  asm volatile(
      "{\n.reg .b32 ra;\n"
      "mapa.shared::cluster.u32 ra, %0, %1;\n"
      "mbarrier.arrive.release.cluster.shared::cluster.b64 _, [ra];\n}\n" ::"r"(bar), "r"(cta)
      : "memory");
}
__device__ __forceinline__ uint32_t mbar_try_wait(uint32_t bar, uint32_t parity) {
  uint32_t ok;
  asm volatile(
      "{\n.reg .pred p;\n"
      "mbarrier.try_wait.parity.shared::cta.b64 p, [%1], %2;\n"
      "selp.u32 %0, 1, 0, p;\n}\n"
      : "=r"(ok)
      : "r"(bar), "r"(parity)
      : "memory");
  return ok;
}
__device__ __forceinline__ void mbar_wait(uint32_t bar, uint32_t parity) {
  if (mbar_try_wait(bar, parity)) return;
  long long t0 = clock64();
  while (!mbar_try_wait(bar, parity)) {
    if (clock64() - t0 > 4000000000LL) __trap();
  }
}
__device__ __forceinline__ void fence_barrier_init() { asm volatile("fence.mbarrier_init.release.cluster;" ::: "memory"); }
__device__ __forceinline__ void fence_proxy_async() { asm volatile("fence.proxy.async.shared::cta;" ::: "memory"); }
__device__ __forceinline__ void cluster_sync_all() {
  asm volatile("barrier.cluster.arrive.release.aligned;\nbarrier.cluster.wait.acquire.aligned;" ::: "memory");
}
__device__ __forceinline__ uint32_t cluster_ctarank() {
  uint32_t r;
  asm volatile("mov.u32 %0, %%cluster_ctarank;" : "=r"(r));
  return r;
}
__device__ __forceinline__ void tma_load_2d(uint32_t dst, const CUtensorMap* map, uint32_t bar, int c0, int c1) {
  asm volatile(
      "cp.async.bulk.tensor.2d.shared::cluster.global.mbarrier::complete_tx::bytes [%0], [%1, {%3, %4}], [%2];" ::"r"(dst),
      "l"(map), "r"(bar), "r"(c0), "r"(c1)
      : "memory");
}
__device__ __forceinline__ void tma_load_2d_mc(uint32_t dst, const CUtensorMap* map, uint32_t bar, int c0, int c1, uint16_t mask) {
  asm volatile(
      "cp.async.bulk.tensor.2d.shared::cluster.global.mbarrier::complete_tx::bytes.multicast::cluster [%0], [%1, {%3, %4}], [%2], %5;" ::"r"(dst),
      "l"(map), "r"(bar), "r"(c0), "r"(c1), "h"(mask)
      : "memory");
}
__device__ __forceinline__ void prefetch_tmap(const CUtensorMap* map) {
  asm volatile("prefetch.tensormap [%0];" ::"l"(map) : "memory");
}
__device__ __forceinline__ void wgmma_fence() { asm volatile("wgmma.fence.sync.aligned;" ::: "memory"); }
__device__ __forceinline__ void wgmma_commit() { asm volatile("wgmma.commit_group.sync.aligned;" ::: "memory"); }
template <int N>
__device__ __forceinline__ void wgmma_wait() {
  asm volatile("wgmma.wait_group.sync.aligned %0;" ::"n"(N) : "memory");
}
template <int R>
__device__ __forceinline__ void reg_alloc() { asm volatile("setmaxnreg.inc.sync.aligned.u32 %0;" ::"n"(R)); }
template <int R>
__device__ __forceinline__ void reg_dealloc() { asm volatile("setmaxnreg.dec.sync.aligned.u32 %0;" ::"n"(R)); }

__device__ __forceinline__ uint64_t make_desc(uint32_t saddr, uint32_t lbo_bytes, uint32_t sbo_bytes, uint32_t layout) {
  uint64_t d = 0;
  d |= (uint64_t)((saddr & 0x3FFFF) >> 4);
  d |= (uint64_t)((lbo_bytes >> 4) & 0x3FFF) << 16;
  d |= (uint64_t)((sbo_bytes >> 4) & 0x3FFF) << 32;
  d |= (uint64_t)layout << 62;
  return d;
}
__device__ __forceinline__ uint32_t pack_bf16(float lo, float hi) {
  __nv_bfloat162 v = __floats2bfloat162_rn(lo, hi);
  return *reinterpret_cast<uint32_t*>(&v);
}
__device__ __forceinline__ float ex2(float x) {
  float y;
  asm("ex2.approx.ftz.f32 %0, %1;" : "=f"(y) : "f"(x));
  return y;
}
__device__ __forceinline__ float gelu_tanh(float x) {
  float u = x * fmaf(0.0356774081f * x, x, 0.7978845608f);
  float t;
  asm("tanh.approx.f32 %0, %1;" : "=f"(t) : "f"(u));
  float hx = 0.5f * x;
  return fmaf(hx, t, hx);
}

__device__ __forceinline__ void wgmma_m64n256k16_ss(float (&d)[128], uint64_t descA, uint64_t descB, int scaleD) {
  asm volatile("{\n.reg .pred p;\n"
    "setp.ne.b32 p, %130, 0;\n"
    "wgmma.mma_async.sync.aligned.m64n256k16.f32.bf16.bf16 "
    "{%0, %1, %2, %3, %4, %5, %6, %7, %8, %9, %10, %11, %12, %13, %14, %15, %16, %17, %18, %19, %20, %21, %22, %23, %24, %25, %26, %27, %28, %29, %30, %31, %32, %33, %34, %35, %36, %37, %38, %39, %40, %41, %42, %43, %44, %45, %46, %47, %48, %49, %50, %51, %52, %53, %54, %55, %56, %57, %58, %59, %60, %61, %62, %63, %64, %65, %66, %67, %68, %69, %70, %71, %72, %73, %74, %75, %76, %77, %78, %79, %80, %81, %82, %83, %84, %85, %86, %87, %88, %89, %90, %91, %92, %93, %94, %95, %96, %97, %98, %99, %100, %101, %102, %103, %104, %105, %106, %107, %108, %109, %110, %111, %112, %113, %114, %115, %116, %117, %118, %119, %120, %121, %122, %123, %124, %125, %126, %127}, "
    "%128, %129, p, 1, 1, 0, 1;\n}\n"
    : "+f"(d[0]), "+f"(d[1]), "+f"(d[2]), "+f"(d[3]), "+f"(d[4]), "+f"(d[5]), "+f"(d[6]), "+f"(d[7]), "+f"(d[8]), "+f"(d[9]), "+f"(d[10]), "+f"(d[11]), "+f"(d[12]), "+f"(d[13]), "+f"(d[14]), "+f"(d[15]), "+f"(d[16]), "+f"(d[17]), "+f"(d[18]), "+f"(d[19]), "+f"(d[20]), "+f"(d[21]), "+f"(d[22]), "+f"(d[23]), "+f"(d[24]), "+f"(d[25]), "+f"(d[26]), "+f"(d[27]), "+f"(d[28]), "+f"(d[29]), "+f"(d[30]), "+f"(d[31]), "+f"(d[32]), "+f"(d[33]), "+f"(d[34]), "+f"(d[35]), "+f"(d[36]), "+f"(d[37]), "+f"(d[38]), "+f"(d[39]), "+f"(d[40]), "+f"(d[41]), "+f"(d[42]), "+f"(d[43]), "+f"(d[44]), "+f"(d[45]), "+f"(d[46]), "+f"(d[47]), "+f"(d[48]), "+f"(d[49]), "+f"(d[50]), "+f"(d[51]), "+f"(d[52]), "+f"(d[53]), "+f"(d[54]), "+f"(d[55]), "+f"(d[56]), "+f"(d[57]), "+f"(d[58]), "+f"(d[59]), "+f"(d[60]), "+f"(d[61]), "+f"(d[62]), "+f"(d[63]), "+f"(d[64]), "+f"(d[65]), "+f"(d[66]), "+f"(d[67]), "+f"(d[68]), "+f"(d[69]), "+f"(d[70]), "+f"(d[71]), "+f"(d[72]), "+f"(d[73]), "+f"(d[74]), "+f"(d[75]), "+f"(d[76]), "+f"(d[77]), "+f"(d[78]), "+f"(d[79]), "+f"(d[80]), "+f"(d[81]), "+f"(d[82]), "+f"(d[83]), "+f"(d[84]), "+f"(d[85]), "+f"(d[86]), "+f"(d[87]), "+f"(d[88]), "+f"(d[89]), "+f"(d[90]), "+f"(d[91]), "+f"(d[92]), "+f"(d[93]), "+f"(d[94]), "+f"(d[95]), "+f"(d[96]), "+f"(d[97]), "+f"(d[98]), "+f"(d[99]), "+f"(d[100]), "+f"(d[101]), "+f"(d[102]), "+f"(d[103]), "+f"(d[104]), "+f"(d[105]), "+f"(d[106]), "+f"(d[107]), "+f"(d[108]), "+f"(d[109]), "+f"(d[110]), "+f"(d[111]), "+f"(d[112]), "+f"(d[113]), "+f"(d[114]), "+f"(d[115]), "+f"(d[116]), "+f"(d[117]), "+f"(d[118]), "+f"(d[119]), "+f"(d[120]), "+f"(d[121]), "+f"(d[122]), "+f"(d[123]), "+f"(d[124]), "+f"(d[125]), "+f"(d[126]), "+f"(d[127])
    : "l"(descA), "l"(descB), "r"(scaleD));
}

__device__ __forceinline__ void wgmma_m64n128k16_ss(float (&d)[64], uint64_t descA, uint64_t descB, int scaleD) {
  asm volatile("{\n.reg .pred p;\n"
    "setp.ne.b32 p, %66, 0;\n"
    "wgmma.mma_async.sync.aligned.m64n128k16.f32.bf16.bf16 "
    "{%0, %1, %2, %3, %4, %5, %6, %7, %8, %9, %10, %11, %12, %13, %14, %15, %16, %17, %18, %19, %20, %21, %22, %23, %24, %25, %26, %27, %28, %29, %30, %31, %32, %33, %34, %35, %36, %37, %38, %39, %40, %41, %42, %43, %44, %45, %46, %47, %48, %49, %50, %51, %52, %53, %54, %55, %56, %57, %58, %59, %60, %61, %62, %63}, "
    "%64, %65, p, 1, 1, 0, 1;\n}\n"
    : "+f"(d[0]), "+f"(d[1]), "+f"(d[2]), "+f"(d[3]), "+f"(d[4]), "+f"(d[5]), "+f"(d[6]), "+f"(d[7]), "+f"(d[8]), "+f"(d[9]), "+f"(d[10]), "+f"(d[11]), "+f"(d[12]), "+f"(d[13]), "+f"(d[14]), "+f"(d[15]), "+f"(d[16]), "+f"(d[17]), "+f"(d[18]), "+f"(d[19]), "+f"(d[20]), "+f"(d[21]), "+f"(d[22]), "+f"(d[23]), "+f"(d[24]), "+f"(d[25]), "+f"(d[26]), "+f"(d[27]), "+f"(d[28]), "+f"(d[29]), "+f"(d[30]), "+f"(d[31]), "+f"(d[32]), "+f"(d[33]), "+f"(d[34]), "+f"(d[35]), "+f"(d[36]), "+f"(d[37]), "+f"(d[38]), "+f"(d[39]), "+f"(d[40]), "+f"(d[41]), "+f"(d[42]), "+f"(d[43]), "+f"(d[44]), "+f"(d[45]), "+f"(d[46]), "+f"(d[47]), "+f"(d[48]), "+f"(d[49]), "+f"(d[50]), "+f"(d[51]), "+f"(d[52]), "+f"(d[53]), "+f"(d[54]), "+f"(d[55]), "+f"(d[56]), "+f"(d[57]), "+f"(d[58]), "+f"(d[59]), "+f"(d[60]), "+f"(d[61]), "+f"(d[62]), "+f"(d[63])
    : "l"(descA), "l"(descB), "r"(scaleD));
}

__device__ __forceinline__ void wgmma_m64n128k16_rs_kmaj(float (&d)[64], uint32_t a0, uint32_t a1, uint32_t a2, uint32_t a3, uint64_t descB, int scaleD) {
  asm volatile("{\n.reg .pred p;\n"
    "setp.ne.b32 p, %69, 0;\n"
    "wgmma.mma_async.sync.aligned.m64n128k16.f32.bf16.bf16 "
    "{%0, %1, %2, %3, %4, %5, %6, %7, %8, %9, %10, %11, %12, %13, %14, %15, %16, %17, %18, %19, %20, %21, %22, %23, %24, %25, %26, %27, %28, %29, %30, %31, %32, %33, %34, %35, %36, %37, %38, %39, %40, %41, %42, %43, %44, %45, %46, %47, %48, %49, %50, %51, %52, %53, %54, %55, %56, %57, %58, %59, %60, %61, %62, %63}, "
    "{%64, %65, %66, %67}, %68, p, 1, 1, 0;\n}\n"
    : "+f"(d[0]), "+f"(d[1]), "+f"(d[2]), "+f"(d[3]), "+f"(d[4]), "+f"(d[5]), "+f"(d[6]), "+f"(d[7]), "+f"(d[8]), "+f"(d[9]), "+f"(d[10]), "+f"(d[11]), "+f"(d[12]), "+f"(d[13]), "+f"(d[14]), "+f"(d[15]), "+f"(d[16]), "+f"(d[17]), "+f"(d[18]), "+f"(d[19]), "+f"(d[20]), "+f"(d[21]), "+f"(d[22]), "+f"(d[23]), "+f"(d[24]), "+f"(d[25]), "+f"(d[26]), "+f"(d[27]), "+f"(d[28]), "+f"(d[29]), "+f"(d[30]), "+f"(d[31]), "+f"(d[32]), "+f"(d[33]), "+f"(d[34]), "+f"(d[35]), "+f"(d[36]), "+f"(d[37]), "+f"(d[38]), "+f"(d[39]), "+f"(d[40]), "+f"(d[41]), "+f"(d[42]), "+f"(d[43]), "+f"(d[44]), "+f"(d[45]), "+f"(d[46]), "+f"(d[47]), "+f"(d[48]), "+f"(d[49]), "+f"(d[50]), "+f"(d[51]), "+f"(d[52]), "+f"(d[53]), "+f"(d[54]), "+f"(d[55]), "+f"(d[56]), "+f"(d[57]), "+f"(d[58]), "+f"(d[59]), "+f"(d[60]), "+f"(d[61]), "+f"(d[62]), "+f"(d[63])
    : "r"(a0), "r"(a1), "r"(a2), "r"(a3), "l"(descB), "r"(scaleD));
}

__device__ __forceinline__ void wgmma_m64n32k16_rs_mnmaj(float (&d)[16], uint32_t a0, uint32_t a1, uint32_t a2, uint32_t a3, uint64_t descB, int scaleD) {
  asm volatile("{\n.reg .pred p;\n"
    "setp.ne.b32 p, %21, 0;\n"
    "wgmma.mma_async.sync.aligned.m64n32k16.f32.bf16.bf16 "
    "{%0, %1, %2, %3, %4, %5, %6, %7, %8, %9, %10, %11, %12, %13, %14, %15}, "
    "{%16, %17, %18, %19}, %20, p, 1, 1, 1;\n}\n"
    : "+f"(d[0]), "+f"(d[1]), "+f"(d[2]), "+f"(d[3]), "+f"(d[4]), "+f"(d[5]), "+f"(d[6]), "+f"(d[7]), "+f"(d[8]), "+f"(d[9]), "+f"(d[10]), "+f"(d[11]), "+f"(d[12]), "+f"(d[13]), "+f"(d[14]), "+f"(d[15])
    : "r"(a0), "r"(a1), "r"(a2), "r"(a3), "l"(descB), "r"(scaleD));
}

__global__ void __launch_bounds__(256) ln_kernel(const bf16* __restrict__ x, bf16* __restrict__ xn) {
  int warp = threadIdx.x >> 5, lane = threadIdx.x & 31;
  int row = blockIdx.x * 8 + warp;
  const uint4* px = reinterpret_cast<const uint4*>(x + (size_t)row * DM);
  float v[32];
#pragma unroll
  for (int i = 0; i < 4; i++) {
    uint4 u = __ldg(px + i * 32 + lane);
    uint32_t w[4] = {u.x, u.y, u.z, u.w};
#pragma unroll
    for (int k = 0; k < 4; k++) {
      v[i * 8 + 2 * k] = __uint_as_float(w[k] << 16);
      v[i * 8 + 2 * k + 1] = __uint_as_float(w[k] & 0xffff0000u);
    }
  }
  float s = 0.f;
#pragma unroll
  for (int i = 0; i < 32; i++) s += v[i];
#pragma unroll
  for (int o = 16; o > 0; o >>= 1) s += __shfl_xor_sync(0xffffffffu, s, o);
  float mean = s * (1.0f / DM);
  float q = 0.f;
#pragma unroll
  for (int i = 0; i < 32; i++) {
    float d = v[i] - mean;
    q = fmaf(d, d, q);
  }
#pragma unroll
  for (int o = 16; o > 0; o >>= 1) q += __shfl_xor_sync(0xffffffffu, q, o);
  float rstd = rsqrtf(q * (1.0f / DM) + 1e-5f);
  uint4* po = reinterpret_cast<uint4*>(xn + (size_t)row * DM);
#pragma unroll
  for (int i = 0; i < 4; i++) {
    uint4 u;
    u.x = pack_bf16((v[i * 8 + 0] - mean) * rstd, (v[i * 8 + 1] - mean) * rstd);
    u.y = pack_bf16((v[i * 8 + 2] - mean) * rstd, (v[i * 8 + 3] - mean) * rstd);
    u.z = pack_bf16((v[i * 8 + 4] - mean) * rstd, (v[i * 8 + 5] - mean) * rstd);
    u.w = pack_bf16((v[i * 8 + 6] - mean) * rstd, (v[i * 8 + 7] - mean) * rstd);
    po[i * 32 + lane] = u;
  }
}

constexpr int G1_STAGES = 4;
constexpr int G1_A_BYTES = 128 * 64 * 2;
constexpr int G1_B_BYTES = 64 * 256 * 2;
constexpr int G1_STAGE_BYTES = G1_A_BYTES + G1_B_BYTES;
constexpr int G1_SMEM = G1_STAGES * G1_STAGE_BYTES + 1024   + 256  ;
constexpr int G1_NTILES_QKV = 12;
constexpr int G1_NTILES_FFN = 28;

template <int CL>
__global__ void __launch_bounds__(384, 1)
    gemm1_kernel(const __grid_constant__ CUtensorMap mapA, const __grid_constant__ CUtensorMap mapWqkv,
                 const __grid_constant__ CUtensorMap mapWg, const __grid_constant__ CUtensorMap mapWu,
                 bf16* __restrict__ qkv, bf16* __restrict__ hbuf) {
  extern __shared__ uint8_t smem_raw[];
  uint32_t sbase = (smem_u32(smem_raw) + 1023u) & ~1023u;
  uint32_t bar_base = sbase + G1_STAGES * G1_STAGE_BYTES;
  const int wg = threadIdx.x >> 7;
  const int warp = threadIdx.x >> 5, lane = threadIdx.x & 31;
  const uint32_t cta_rank = (CL > 1) ? cluster_ctarank() : 0;
  const int cluster_id = blockIdx.x / CL;
  const int n_clusters = gridDim.x / CL;
  constexpr int MG = 16 / CL;
  constexpr int N_CT = (G1_NTILES_QKV + G1_NTILES_FFN) * MG;

  if (threadIdx.x == 0) {
    for (int s = 0; s < G1_STAGES; s++) {
      mbar_init(bar_base + 8 * s, 1);
      mbar_init(bar_base + 64 + 8 * s, CL * 8);
    }
    fence_barrier_init();
  }
  __syncthreads();
  if (CL > 1) cluster_sync_all();

  if (wg == 0) {
    reg_dealloc<40>();
    if (warp == 0 && lane == 0) {
      prefetch_tmap(&mapA); prefetch_tmap(&mapWqkv); prefetch_tmap(&mapWg); prefetch_tmap(&mapWu);
      int stage = 0, phase = 0;
      for (int ct = cluster_id; ct < N_CT; ct += n_clusters) {
        int n_blk = ct / MG;
        int m_blk = (ct % MG) * CL + cta_rank;
        bool ffn = n_blk >= G1_NTILES_QKV;
        for (int kb = 0; kb < 16; kb++) {
          uint32_t full = bar_base + 8 * stage, empty = bar_base + 64 + 8 * stage;
          mbar_wait(empty, phase ^ 1);
          mbar_expect_tx(full, G1_STAGE_BYTES);
          uint32_t sa = sbase + stage * G1_STAGE_BYTES;
          uint32_t sb = sa + G1_A_BYTES;
          tma_load_2d(sa, &mapA, full, kb * 64, m_blk * 128);
#pragma unroll
          for (int i = 0; i < 4 / CL; i++) {
            int bi = cta_rank * (4 / CL) + i;
            const CUtensorMap* mp;
            int col;
            if (!ffn) { mp = &mapWqkv; col = n_blk * 256 + bi * 64; }
            else { mp = (bi < 2) ? &mapWg : &mapWu; col = (n_blk - G1_NTILES_QKV) * 128 + (bi & 1) * 64; }
            if (CL > 1) tma_load_2d_mc(sb + bi * 8192, mp, full, col, kb * 64, (uint16_t)((1 << CL) - 1));
            else tma_load_2d(sb + bi * 8192, mp, full, col, kb * 64);
          }
          if (++stage == G1_STAGES) { stage = 0; phase ^= 1; }
        }
      }
    }
  } else {
    reg_alloc<232>();
    const int cw = wg - 1;
    const int wq = warp & 3, g = lane >> 2, q = lane & 3;
    int stage = 0, phase = 0;
    float acc[128];
    for (int ct = cluster_id; ct < N_CT; ct += n_clusters) {
      int n_blk = ct / MG;
      int m_blk = (ct % MG) * CL + cta_rank;
      bool ffn = n_blk >= G1_NTILES_QKV;
      int prev_stage = 0;
      for (int kb = 0; kb < 16; kb++) {
        uint32_t full = bar_base + 8 * stage;
        mbar_wait(full, phase);
        uint32_t sa = sbase + stage * G1_STAGE_BYTES;
        uint64_t descA = make_desc(sa + cw * 8192, 16, 1024, 1);
        uint64_t descB = make_desc(sa + G1_A_BYTES, 8192, 1024, 1);
        wgmma_fence();
#pragma unroll
        for (int k = 0; k < 4; k++) {
          wgmma_m64n256k16_ss(acc, descA + (uint64_t)(k * 2), descB + (uint64_t)(k * 128), (kb | k) != 0);
        }
        wgmma_commit();
        if (kb > 0) {
          wgmma_wait<1>();
          uint32_t empty = bar_base + 64 + 8 * prev_stage;
          if (CL > 1) { if (lane < CL) mbar_arrive_cluster(empty, lane); }
          else { if (lane == 0) mbar_arrive(empty); }
        }
        prev_stage = stage;
        if (++stage == G1_STAGES) { stage = 0; phase ^= 1; }
      }
      wgmma_wait<0>();
      {
        uint32_t empty = bar_base + 64 + 8 * prev_stage;
        if (CL > 1) { if (lane < CL) mbar_arrive_cluster(empty, lane); }
        else { if (lane == 0) mbar_arrive(empty); }
      }
      int row0 = m_blk * 128 + cw * 64 + wq * 16 + g;
      if (!ffn) {
        bf16* p0 = qkv + (size_t)row0 * (3 * DM) + n_blk * 256 + 2 * q;
        bf16* p1 = p0 + 8 * (3 * DM);
#pragma unroll
        for (int j = 0; j < 32; j++) {
          *reinterpret_cast<uint32_t*>(p0 + 8 * j) = pack_bf16(acc[4 * j], acc[4 * j + 1]);
          *reinterpret_cast<uint32_t*>(p1 + 8 * j) = pack_bf16(acc[4 * j + 2], acc[4 * j + 3]);
        }
      } else {
        bf16* p0 = hbuf + (size_t)row0 * FF + (n_blk - G1_NTILES_QKV) * 128 + 2 * q;
        bf16* p1 = p0 + 8 * FF;
#pragma unroll
        for (int j = 0; j < 16; j++) {
          float h0 = gelu_tanh(acc[4 * j]) * acc[64 + 4 * j];
          float h1 = gelu_tanh(acc[4 * j + 1]) * acc[64 + 4 * j + 1];
          float h2 = gelu_tanh(acc[4 * j + 2]) * acc[64 + 4 * j + 2];
          float h3 = gelu_tanh(acc[4 * j + 3]) * acc[64 + 4 * j + 3];
          *reinterpret_cast<uint32_t*>(p0 + 8 * j) = pack_bf16(h0, h1);
          *reinterpret_cast<uint32_t*>(p1 + 8 * j) = pack_bf16(h2, h3);
        }
      }
    }
  }
  if (CL > 1) cluster_sync_all();
}

constexpr int AT_STAGES = 4;
constexpr int AT_TILE_BYTES = 128 * 64;
constexpr int AT_SMEM = AT_STAGES * 2 * AT_TILE_BYTES + 1024 + 256;
constexpr int AT_THREADS = 512;

__global__ void __launch_bounds__(AT_THREADS, 1)
    attn_kernel(const __grid_constant__ CUtensorMap mapKV, const bf16* __restrict__ qkv, bf16* __restrict__ o) {
  extern __shared__ uint8_t smem_raw[];
  uint32_t sbase = (smem_u32(smem_raw) + 1023u) & ~1023u;
  uint32_t bar_base = sbase + AT_STAGES * 2 * AT_TILE_BYTES;
  const int warp = threadIdx.x >> 5, lane = threadIdx.x & 31;
  const int head = blockIdx.x >> 3, qblk = blockIdx.x & 7;
  if (threadIdx.x == 0) {
    for (int s = 0; s < AT_STAGES; s++) {
      mbar_init(bar_base + 8 * s, 1);
      mbar_init(bar_base + 64 + 8 * s, 1);
      mbar_init(bar_base + 128 + 8 * s, 16);
    }
    fence_barrier_init();
  }
  __syncthreads();
  constexpr int NT = SEQ / 128;

  constexpr int LA = 2;
  auto issue_tile = [&](int jn) {
    int s = jn & (AT_STAGES - 1), ph = (jn / AT_STAGES) & 1;
    mbar_wait(bar_base + 128 + 8 * s, ph ^ 1);
    uint32_t sk = sbase + s * 2 * AT_TILE_BYTES;
    mbar_expect_tx(bar_base + 8 * s, AT_TILE_BYTES);
    tma_load_2d(sk, &mapKV, bar_base + 8 * s, DM + head * DH, jn * 128);
    mbar_expect_tx(bar_base + 64 + 8 * s, AT_TILE_BYTES);
    tma_load_2d(sk + AT_TILE_BYTES, &mapKV, bar_base + 64 + 8 * s, 2 * DM + head * DH, jn * 128);
  };
  if (threadIdx.x == 0) {
    prefetch_tmap(&mapKV);
    for (int jn = 0; jn < LA; jn++) issue_tile(jn);
  }

  const int wg = warp >> 2, wq = warp & 3, g = lane >> 2, q = lane & 3;
  const int row0 = qblk * 256 + wg * 64 + wq * 16 + g;
  uint32_t qf[2][4];
  {
    const bf16* qp = qkv + (size_t)row0 * (3 * DM) + head * DH + 2 * q;
#pragma unroll
    for (int kk = 0; kk < 2; kk++) {
      qf[kk][0] = *reinterpret_cast<const uint32_t*>(qp + kk * 16);
      qf[kk][1] = *reinterpret_cast<const uint32_t*>(qp + 8 * 3 * DM + kk * 16);
      qf[kk][2] = *reinterpret_cast<const uint32_t*>(qp + kk * 16 + 8);
      qf[kk][3] = *reinterpret_cast<const uint32_t*>(qp + 8 * 3 * DM + kk * 16 + 8);
    }
  }
  const float sl2 = 0.17677669529663687f * 1.4426950408889634f;
  float oacc[16];
#pragma unroll
  for (int i = 0; i < 16; i++) oacc[i] = 0.f;
  float m0 = -INFINITY, m1 = -INFINITY, l0 = 0.f, l1 = 0.f;

  for (int j = 0; j < NT; j++) {
    int s = j & (AT_STAGES - 1), ph = (j / AT_STAGES) & 1;
    uint32_t sk = sbase + s * 2 * AT_TILE_BYTES;
    float sc[64];
    if (threadIdx.x == 0 && j + LA < NT) issue_tile(j + LA);
    __syncwarp();
    mbar_wait(bar_base + 8 * s, ph);
    {
      uint64_t descK = make_desc(sk, 16, 512, 2);
      wgmma_fence();
      wgmma_m64n128k16_rs_kmaj(sc, qf[0][0], qf[0][1], qf[0][2], qf[0][3], descK, 0);
      wgmma_m64n128k16_rs_kmaj(sc, qf[1][0], qf[1][1], qf[1][2], qf[1][3], descK + 2, 1);
      wgmma_commit();
      wgmma_wait<0>();
    }
    float mx0 = fmaxf(sc[0], sc[1]), mx1 = fmaxf(sc[2], sc[3]);
#pragma unroll
    for (int i = 1; i < 16; i++) {
      mx0 = fmaxf(mx0, fmaxf(sc[4 * i], sc[4 * i + 1]));
      mx1 = fmaxf(mx1, fmaxf(sc[4 * i + 2], sc[4 * i + 3]));
    }
    mx0 = fmaxf(mx0, __shfl_xor_sync(0xffffffffu, mx0, 1));
    mx1 = fmaxf(mx1, __shfl_xor_sync(0xffffffffu, mx1, 1));
    mx0 = fmaxf(mx0, __shfl_xor_sync(0xffffffffu, mx0, 2));
    mx1 = fmaxf(mx1, __shfl_xor_sync(0xffffffffu, mx1, 2));
    float mn0 = fmaxf(m0, mx0), mn1 = fmaxf(m1, mx1);
    float a0 = ex2((m0 - mn0) * sl2), a1 = ex2((m1 - mn1) * sl2);
    m0 = mn0; m1 = mn1;
    float nb0 = -mn0 * sl2, nb1 = -mn1 * sl2;
    float s0 = 0.f, s1 = 0.f;
    uint32_t pf[32];
#pragma unroll
    for (int i = 0; i < 16; i++) {
      float p0 = ex2(fmaf(sc[4 * i], sl2, nb0));
      float p1 = ex2(fmaf(sc[4 * i + 1], sl2, nb0));
      float p2 = ex2(fmaf(sc[4 * i + 2], sl2, nb1));
      float p3 = ex2(fmaf(sc[4 * i + 3], sl2, nb1));
      s0 += p0 + p1;
      s1 += p2 + p3;
      pf[2 * i] = pack_bf16(p0, p1);
      pf[2 * i + 1] = pack_bf16(p2, p3);
    }
    l0 = fmaf(l0, a0, s0);
    l1 = fmaf(l1, a1, s1);
#pragma unroll
    for (int i = 0; i < 4; i++) {
      oacc[4 * i] *= a0; oacc[4 * i + 1] *= a0; oacc[4 * i + 2] *= a1; oacc[4 * i + 3] *= a1;
    }
    mbar_wait(bar_base + 64 + 8 * s, ph);
    {
      uint64_t descV = make_desc(sk + AT_TILE_BYTES, 16, 512, 2);
      wgmma_fence();
#pragma unroll
      for (int kk = 0; kk < 8; kk++) {
        wgmma_m64n32k16_rs_mnmaj(oacc, pf[4 * kk], pf[4 * kk + 1], pf[4 * kk + 2], pf[4 * kk + 3], descV + (uint64_t)(kk * 64), 1);
      }
      wgmma_commit();
      wgmma_wait<0>();
    }
    if (lane == 0) mbar_arrive(bar_base + 128 + 8 * s);
  }
  l0 += __shfl_xor_sync(0xffffffffu, l0, 1);
  l1 += __shfl_xor_sync(0xffffffffu, l1, 1);
  l0 += __shfl_xor_sync(0xffffffffu, l0, 2);
  l1 += __shfl_xor_sync(0xffffffffu, l1, 2);
  float inv0 = 1.0f / l0, inv1 = 1.0f / l1;
  bf16* op = o + (size_t)row0 * DM + head * DH + 2 * q;
#pragma unroll
  for (int i = 0; i < 4; i++) {
    *reinterpret_cast<uint32_t*>(op + 8 * i) = pack_bf16(oacc[4 * i] * inv0, oacc[4 * i + 1] * inv0);
    *reinterpret_cast<uint32_t*>(op + 8 * DM + 8 * i) = pack_bf16(oacc[4 * i + 2] * inv1, oacc[4 * i + 3] * inv1);
  }
}

constexpr int G2_STAGES = 6;
constexpr int G2_A_BYTES = 128 * 64 * 2;
constexpr int G2_B_BYTES = 64 * 128 * 2;
constexpr int G2_STAGE_BYTES = G2_A_BYTES + G2_B_BYTES;
constexpr int G2_SMEM = G2_STAGES * G2_STAGE_BYTES + 1024 + 256;
constexpr int G2_KB1 = FF / 64;
constexpr int G2_KB2 = DM / 64;

template <int CL>
__global__ void __launch_bounds__(384, 1)
    gemm2_kernel(const __grid_constant__ CUtensorMap mapH, const __grid_constant__ CUtensorMap mapWd,
                 const __grid_constant__ CUtensorMap mapO, const __grid_constant__ CUtensorMap mapWo,
                 const bf16* __restrict__ x, bf16* __restrict__ out) {
  extern __shared__ uint8_t smem_raw[];
  uint32_t sbase = (smem_u32(smem_raw) + 1023u) & ~1023u;
  uint32_t bar_base = sbase + G2_STAGES * G2_STAGE_BYTES;
  const int wg = threadIdx.x >> 7;
  const int warp = threadIdx.x >> 5, lane = threadIdx.x & 31;
  const uint32_t cta_rank = (CL > 1) ? cluster_ctarank() : 0;
  const int cluster_id = blockIdx.x / CL;
  constexpr int MG = 16 / CL;
  const int n_blk = cluster_id / MG;
  const int m_blk = (cluster_id % MG) * CL + cta_rank;

  if (threadIdx.x == 0) {
    for (int s = 0; s < G2_STAGES; s++) {
      mbar_init(bar_base + 8 * s, 1);
      mbar_init(bar_base + 64 + 8 * s, CL * 8);
    }
    fence_barrier_init();
  }
  __syncthreads();
  if (CL > 1) cluster_sync_all();

  if (wg == 0) {
    reg_dealloc<40>();
    if (warp == 0 && lane == 0) {
      prefetch_tmap(&mapH); prefetch_tmap(&mapWd); prefetch_tmap(&mapO); prefetch_tmap(&mapWo);
      int stage = 0, phase = 0;
      for (int kb = 0; kb < G2_KB1 + G2_KB2; kb++) {
        uint32_t full = bar_base + 8 * stage, empty = bar_base + 64 + 8 * stage;
        mbar_wait(empty, phase ^ 1);
        mbar_expect_tx(full, G2_STAGE_BYTES);
        uint32_t sa = sbase + stage * G2_STAGE_BYTES;
        uint32_t sb = sa + G2_A_BYTES;
        bool first = kb < G2_KB1;
        const CUtensorMap* ma = first ? &mapH : &mapO;
        const CUtensorMap* mb = first ? &mapWd : &mapWo;
        int k0 = (first ? kb : kb - G2_KB1) * 64;
        tma_load_2d(sa, ma, full, k0, m_blk * 128);
#pragma unroll
        for (int i = 0; i < 4 / CL; i++) {
          int bi = cta_rank * (4 / CL) + i;
          uint32_t dst = sb + (bi & 1) * 8192 + (bi >> 1) * 4096;
          int col = n_blk * 128 + (bi & 1) * 64;
          int krow = k0 + (bi >> 1) * 32;
          if (CL > 1) tma_load_2d_mc(dst, mb, full, col, krow, (uint16_t)((1 << CL) - 1));
          else tma_load_2d(dst, mb, full, col, krow);
        }
        if (++stage == G2_STAGES) { stage = 0; phase ^= 1; }
      }
    }
  } else {
    reg_alloc<232>();
    const int cw = wg - 1;
    const int wq = warp & 3, g = lane >> 2, q = lane & 3;
    int stage = 0, phase = 0, prev_stage = 0;
    float accf[64], accs[64];
    for (int kb = 0; kb < G2_KB1; kb++) {
      mbar_wait(bar_base + 8 * stage, phase);
      uint32_t sa = sbase + stage * G2_STAGE_BYTES;
      uint64_t descA = make_desc(sa + cw * 8192, 16, 1024, 1);
      uint64_t descB = make_desc(sa + G2_A_BYTES, 8192, 1024, 1);
      wgmma_fence();
#pragma unroll
      for (int k = 0; k < 4; k++) wgmma_m64n128k16_ss(accf, descA + (uint64_t)(k * 2), descB + (uint64_t)(k * 128), (kb | k) != 0);
      wgmma_commit();
      if (kb > 0) {
        wgmma_wait<1>();
        uint32_t empty = bar_base + 64 + 8 * prev_stage;
        if (CL > 1) { if (lane < CL) mbar_arrive_cluster(empty, lane); }
        else { if (lane == 0) mbar_arrive(empty); }
      }
      prev_stage = stage;
      if (++stage == G2_STAGES) { stage = 0; phase ^= 1; }
    }
    for (int kb = 0; kb < G2_KB2; kb++) {
      mbar_wait(bar_base + 8 * stage, phase);
      uint32_t sa = sbase + stage * G2_STAGE_BYTES;
      uint64_t descA = make_desc(sa + cw * 8192, 16, 1024, 1);
      uint64_t descB = make_desc(sa + G2_A_BYTES, 8192, 1024, 1);
      wgmma_fence();
#pragma unroll
      for (int k = 0; k < 4; k++) wgmma_m64n128k16_ss(accs, descA + (uint64_t)(k * 2), descB + (uint64_t)(k * 128), (kb | k) != 0);
      wgmma_commit();
      wgmma_wait<1>();
      {
        uint32_t empty = bar_base + 64 + 8 * prev_stage;
        if (CL > 1) { if (lane < CL) mbar_arrive_cluster(empty, lane); }
        else { if (lane == 0) mbar_arrive(empty); }
      }
      prev_stage = stage;
      if (++stage == G2_STAGES) { stage = 0; phase ^= 1; }
    }
    wgmma_wait<0>();
    int row0 = m_blk * 128 + cw * 64 + wq * 16 + g;
    size_t off0 = (size_t)row0 * DM + n_blk * 128 + 2 * q;
#pragma unroll
    for (int j = 0; j < 16; j++) {
#pragma unroll
      for (int hrow = 0; hrow < 2; hrow++) {
        size_t off = off0 + hrow * 8 * DM + 8 * j;
        uint32_t xv = *reinterpret_cast<const uint32_t*>(x + off);
        float x0 = __uint_as_float(xv << 16), x1 = __uint_as_float(xv & 0xffff0000u);
        float f0 = accf[4 * j + 2 * hrow], f1 = accf[4 * j + 2 * hrow + 1];
        float s0 = accs[4 * j + 2 * hrow], s1 = accs[4 * j + 2 * hrow + 1];
        float g0 = f0 / (1.0f + __expf(-f0));
        float g1 = f1 / (1.0f + __expf(-f1));
        *reinterpret_cast<uint32_t*>(out + off) = pack_bf16(fmaf(s0, g0, x0), fmaf(s1, g1, x1));
      }
    }
  }
  if (CL > 1) { asm volatile("barrier.cluster.arrive.release;\nbarrier.cluster.wait.acquire;" ::: "memory"); }
}

typedef CUresult (*PFN_encodeTiled)(CUtensorMap*, CUtensorMapDataType, cuuint32_t, void*, const cuuint64_t*, const cuuint64_t*,
                                    const cuuint32_t*, const cuuint32_t*, CUtensorMapInterleave, CUtensorMapSwizzle,
                                    CUtensorMapL2promotion, CUtensorMapFloatOOBfill);

CUtensorMap make_map(PFN_encodeTiled f, const void* ptr, uint64_t inner, uint64_t outer, uint32_t box_inner, uint32_t box_outer,
                     CUtensorMapSwizzle sw) {
  CUtensorMap m;
  cuuint64_t dims[2] = {inner, outer};
  cuuint64_t strides[1] = {inner * 2};
  cuuint32_t box[2] = {box_inner, box_outer};
  cuuint32_t es[2] = {1, 1};
  f(&m, CU_TENSOR_MAP_DATA_TYPE_BFLOAT16, 2, const_cast<void*>(ptr), dims, strides, box, es, CU_TENSOR_MAP_INTERLEAVE_NONE, sw,
    CU_TENSOR_MAP_L2_PROMOTION_L2_256B, CU_TENSOR_MAP_FLOAT_OOB_FILL_NONE);
  return m;
}

template <typename... Args>
void launch_ex(void (*kern)(Args...), int grid, int block, size_t smem, int cluster, Args... args) {
  cudaLaunchConfig_t cfg = {};
  cfg.gridDim = dim3(grid);
  cfg.blockDim = dim3(block);
  cfg.dynamicSmemBytes = smem;
  cfg.stream = cudaStreamPerThread;
  cudaLaunchAttribute attr[1];
  attr[0].id = cudaLaunchAttributeClusterDimension;
  attr[0].val.clusterDim.x = cluster;
  attr[0].val.clusterDim.y = 1;
  attr[0].val.clusterDim.z = 1;
  cfg.attrs = attr;
  cfg.numAttrs = (cluster > 1) ? 1 : 0;
  cudaLaunchKernelEx(&cfg, kern, args...);
}

constexpr int G1_CL = 1;
constexpr int G2_CL = 1;

}

extern "C" void kernel_launch(void* const* d_in, const int* in_sizes, int n_in, void* d_out, int out_size) {
  const bf16* x = (const bf16*)d_in[0];
  const bf16* wqkv = (const bf16*)d_in[1];
  const bf16* wo = (const bf16*)d_in[2];
  const bf16* wg = (const bf16*)d_in[4];
  const bf16* wu = (const bf16*)d_in[5];
  const bf16* wd = (const bf16*)d_in[6];
  bf16* out = (bf16*)d_out;

  static PFN_encodeTiled enc = nullptr;
  static bf16 *p_xn, *p_qkv, *p_h, *p_o;
  if (!enc) {
    void* fn = nullptr;
    cudaDriverEntryPointQueryResult qres;
    cudaGetDriverEntryPoint("cuTensorMapEncodeTiled", &fn, cudaEnableDefault, &qres);
    enc = (PFN_encodeTiled)fn;
    cudaGetSymbolAddress((void**)&p_xn, g_xn);
    cudaGetSymbolAddress((void**)&p_qkv, g_qkv);
    cudaGetSymbolAddress((void**)&p_h, g_h);
    cudaGetSymbolAddress((void**)&p_o, g_o);
    cudaFuncSetAttribute(gemm1_kernel<G1_CL>, cudaFuncAttributeMaxDynamicSharedMemorySize, G1_SMEM);
    cudaFuncSetAttribute(gemm2_kernel<G2_CL>, cudaFuncAttributeMaxDynamicSharedMemorySize, G2_SMEM);
    cudaFuncSetAttribute(attn_kernel, cudaFuncAttributeMaxDynamicSharedMemorySize, AT_SMEM);
  }
  const CUtensorMapSwizzle SW128 = CU_TENSOR_MAP_SWIZZLE_128B, SW64 = CU_TENSOR_MAP_SWIZZLE_64B;
  CUtensorMap mXn = make_map(enc, p_xn, DM, SEQ, 64, 128, SW128);
  CUtensorMap mWqkv = make_map(enc, wqkv, 3 * DM, DM, 64, 64, SW128);
  CUtensorMap mWg = make_map(enc, wg, FF, DM, 64, 64, SW128);
  CUtensorMap mWu = make_map(enc, wu, FF, DM, 64, 64, SW128);
  CUtensorMap mKV = make_map(enc, p_qkv, 3 * DM, SEQ, 32, 128, SW64);
  CUtensorMap mH = make_map(enc, p_h, FF, SEQ, 64, 128, SW128);
  CUtensorMap mWd = make_map(enc, wd, DM, FF, 64, 32, SW128);
  CUtensorMap mO = make_map(enc, p_o, DM, SEQ, 64, 128, SW128);
  CUtensorMap mWo = make_map(enc, wo, DM, DM, 64, 32, SW128);

  ln_kernel<<<SEQ / 8, 256, 0, cudaStreamPerThread>>>(x, p_xn);
  launch_ex(gemm1_kernel<G1_CL>, (G1_CL == 4) ? 128 : 132, 384, G1_SMEM, G1_CL, mXn, mWqkv, mWg, mWu, p_qkv, p_h);
  launch_ex(attn_kernel, 256, AT_THREADS, AT_SMEM, 1, mKV, (const bf16*)p_qkv, p_o);
  launch_ex(gemm2_kernel<G2_CL>, 128, 384, G2_SMEM, G2_CL, mH, mWd, mO, mWo, x, out);
}
```

```cpp
#include <cuda_runtime.h>
#include <cuda_bf16.h>
#include <cuda.h>
#include <stdint.h>

namespace {

typedef __nv_bfloat16 bf16;

constexpr int SEQ = 2048;
constexpr int DM = 1024;
constexpr int FF = 3584;
constexpr int NH = 32;
constexpr int DH = 32;

__device__ bf16 g_xn[SEQ * DM];
__device__ bf16 g_qkv[SEQ * 3 * DM];
__device__ bf16 g_h[SEQ * FF];
__device__ bf16 g_o[SEQ * DM];

__device__ __forceinline__ uint32_t smem_u32(const void* p) { return (uint32_t)__cvta_generic_to_shared(p); }

__device__ __forceinline__ void mbar_init(uint32_t bar, uint32_t count) {
  asm volatile("mbarrier.init.shared::cta.b64 [%0], %1;" ::"r"(bar), "r"(count) : "memory");
}
__device__ __forceinline__ void mbar_expect_tx(uint32_t bar, uint32_t bytes) {
  asm volatile("mbarrier.arrive.expect_tx.shared::cta.b64 _, [%0], %1;" ::"r"(bar), "r"(bytes) : "memory");
}
__device__ __forceinline__ void mbar_arrive(uint32_t bar) {
  asm volatile("mbarrier.arrive.shared::cta.b64 _, [%0];" ::"r"(bar) : "memory");
}
__device__ __forceinline__ void mbar_arrive_cluster(uint32_t bar, uint32_t cta) {
  asm volatile(
      "{\n.reg .b32 ra;\n"
      "mapa.shared::cluster.u32 ra, %0, %1;\n"
      "mbarrier.arrive.shared::cluster.b64 _, [ra];\n}\n" ::"r"(bar), "r"(cta)
      : "memory");
}
__device__ __forceinline__ uint32_t mbar_try_wait(uint32_t bar, uint32_t parity) {
  uint32_t ok;
  asm volatile(
      "{\n.reg .pred p;\n"
      "mbarrier.try_wait.parity.shared::cta.b64 p, [%1], %2;\n"
      "selp.u32 %0, 1, 0, p;\n}\n"
      : "=r"(ok)
      : "r"(bar), "r"(parity)
      : "memory");
  return ok;
}
__device__ __forceinline__ void mbar_wait(uint32_t bar, uint32_t parity) {
  if (mbar_try_wait(bar, parity)) return;
  long long t0 = clock64();
  while (!mbar_try_wait(bar, parity)) {
    if (clock64() - t0 > 4000000000LL) __trap();
  }
}
__device__ __forceinline__ void fence_barrier_init() { asm volatile("fence.mbarrier_init.release.cluster;" ::: "memory"); }
__device__ __forceinline__ void fence_proxy_async() { asm volatile("fence.proxy.async.shared::cta;" ::: "memory"); }
__device__ __forceinline__ void cluster_sync_all() {
  asm volatile("barrier.cluster.arrive.release.aligned;\nbarrier.cluster.wait.acquire.aligned;" ::: "memory");
}
__device__ __forceinline__ uint32_t cluster_ctarank() {
  uint32_t r;
  asm volatile("mov.u32 %0, %%cluster_ctarank;" : "=r"(r));
  return r;
}
__device__ __forceinline__ void tma_load_2d(uint32_t dst, const CUtensorMap* map, uint32_t bar, int c0, int c1) {
  asm volatile(
      "cp.async.bulk.tensor.2d.shared::cluster.global.mbarrier::complete_tx::bytes [%0], [%1, {%3, %4}], [%2];" ::"r"(dst),
      "l"(map), "r"(bar), "r"(c0), "r"(c1)
      : "memory");
}
__device__ __forceinline__ void tma_load_2d_mc(uint32_t dst, const CUtensorMap* map, uint32_t bar, int c0, int c1, uint16_t mask) {
  asm volatile(
      "cp.async.bulk.tensor.2d.shared::cluster.global.mbarrier::complete_tx::bytes.multicast::cluster [%0], [%1, {%3, %4}], [%2], %5;" ::"r"(dst),
      "l"(map), "r"(bar), "r"(c0), "r"(c1), "h"(mask)
      : "memory");
}
__device__ __forceinline__ void tma_store_2d(const CUtensorMap* map, uint32_t src, int c0, int c1) {
  asm volatile("cp.async.bulk.tensor.2d.global.shared::cta.bulk_group [%0, {%2, %3}], [%1];" ::"l"(map), "r"(src), "r"(c0), "r"(c1)
               : "memory");
}
__device__ __forceinline__ void bulk_commit() { asm volatile("cp.async.bulk.commit_group;" ::: "memory"); }
__device__ __forceinline__ void bulk_wait_read0() { asm volatile("cp.async.bulk.wait_group.read 0;" ::: "memory"); }
__device__ __forceinline__ void bulk_wait0() { asm volatile("cp.async.bulk.wait_group 0;" ::: "memory"); }
__device__ __forceinline__ void named_bar(int id, int n) { asm volatile("bar.sync %0, %1;" ::"r"(id), "r"(n) : "memory"); }
__device__ __forceinline__ void stmatrix_x4(uint32_t addr, uint32_t r0, uint32_t r1, uint32_t r2, uint32_t r3) {
  asm volatile("stmatrix.sync.aligned.m8n8.x4.shared.b16 [%0], {%1, %2, %3, %4};" ::"r"(addr), "r"(r0), "r"(r1), "r"(r2), "r"(r3)
               : "memory");
}
__device__ __forceinline__ void prefetch_tmap(const CUtensorMap* map) {
  asm volatile("prefetch.tensormap [%0];" ::"l"(map) : "memory");
}
__device__ __forceinline__ void wgmma_fence() { asm volatile("wgmma.fence.sync.aligned;" ::: "memory"); }
__device__ __forceinline__ void wgmma_commit() { asm volatile("wgmma.commit_group.sync.aligned;" ::: "memory"); }
template <int N>
__device__ __forceinline__ void wgmma_wait() {
  asm volatile("wgmma.wait_group.sync.aligned %0;" ::"n"(N) : "memory");
}
template <int R>
__device__ __forceinline__ void reg_alloc() { asm volatile("setmaxnreg.inc.sync.aligned.u32 %0;" ::"n"(R)); }
template <int R>
__device__ __forceinline__ void reg_dealloc() { asm volatile("setmaxnreg.dec.sync.aligned.u32 %0;" ::"n"(R)); }

__device__ __forceinline__ uint64_t make_desc(uint32_t saddr, uint32_t lbo_bytes, uint32_t sbo_bytes, uint32_t layout) {
  uint64_t d = 0;
  d |= (uint64_t)((saddr & 0x3FFFF) >> 4);
  d |= (uint64_t)((lbo_bytes >> 4) & 0x3FFF) << 16;
  d |= (uint64_t)((sbo_bytes >> 4) & 0x3FFF) << 32;
  d |= (uint64_t)layout << 62;
  return d;
}
__device__ __forceinline__ uint32_t pack_bf16(float lo, float hi) {
  __nv_bfloat162 v = __floats2bfloat162_rn(lo, hi);
  return *reinterpret_cast<uint32_t*>(&v);
}
__device__ __forceinline__ float ex2(float x) {
  float y;
  asm("ex2.approx.ftz.f32 %0, %1;" : "=f"(y) : "f"(x));
  return y;
}
__device__ __forceinline__ float gelu_tanh(float x) {
  float u = x * fmaf(0.0356774081f * x, x, 0.7978845608f);
  float e = ex2(-2.8853900817779268f * u);
  return __fdividef(x, 1.0f + e);
}

__device__ __forceinline__ void wgmma_m64n256k16_ss(float (&d)[128], uint64_t descA, uint64_t descB, int scaleD) {
  asm volatile("{\n.reg .pred p;\n"
    "setp.ne.b32 p, %130, 0;\n"
    "wgmma.mma_async.sync.aligned.m64n256k16.f32.bf16.bf16 "
    "{%0, %1, %2, %3, %4, %5, %6, %7, %8, %9, %10, %11, %12, %13, %14, %15, %16, %17, %18, %19, %20, %21, %22, %23, %24, %25, %26, %27, %28, %29, %30, %31, %32, %33, %34, %35, %36, %37, %38, %39, %40, %41, %42, %43, %44, %45, %46, %47, %48, %49, %50, %51, %52, %53, %54, %55, %56, %57, %58, %59, %60, %61, %62, %63, %64, %65, %66, %67, %68, %69, %70, %71, %72, %73, %74, %75, %76, %77, %78, %79, %80, %81, %82, %83, %84, %85, %86, %87, %88, %89, %90, %91, %92, %93, %94, %95, %96, %97, %98, %99, %100, %101, %102, %103, %104, %105, %106, %107, %108, %109, %110, %111, %112, %113, %114, %115, %116, %117, %118, %119, %120, %121, %122, %123, %124, %125, %126, %127}, "
    "%128, %129, p, 1, 1, 0, 1;\n}\n"
    : "+f"(d[0]), "+f"(d[1]), "+f"(d[2]), "+f"(d[3]), "+f"(d[4]), "+f"(d[5]), "+f"(d[6]), "+f"(d[7]), "+f"(d[8]), "+f"(d[9]), "+f"(d[10]), "+f"(d[11]), "+f"(d[12]), "+f"(d[13]), "+f"(d[14]), "+f"(d[15]), "+f"(d[16]), "+f"(d[17]), "+f"(d[18]), "+f"(d[19]), "+f"(d[20]), "+f"(d[21]), "+f"(d[22]), "+f"(d[23]), "+f"(d[24]), "+f"(d[25]), "+f"(d[26]), "+f"(d[27]), "+f"(d[28]), "+f"(d[29]), "+f"(d[30]), "+f"(d[31]), "+f"(d[32]), "+f"(d[33]), "+f"(d[34]), "+f"(d[35]), "+f"(d[36]), "+f"(d[37]), "+f"(d[38]), "+f"(d[39]), "+f"(d[40]), "+f"(d[41]), "+f"(d[42]), "+f"(d[43]), "+f"(d[44]), "+f"(d[45]), "+f"(d[46]), "+f"(d[47]), "+f"(d[48]), "+f"(d[49]), "+f"(d[50]), "+f"(d[51]), "+f"(d[52]), "+f"(d[53]), "+f"(d[54]), "+f"(d[55]), "+f"(d[56]), "+f"(d[57]), "+f"(d[58]), "+f"(d[59]), "+f"(d[60]), "+f"(d[61]), "+f"(d[62]), "+f"(d[63]), "+f"(d[64]), "+f"(d[65]), "+f"(d[66]), "+f"(d[67]), "+f"(d[68]), "+f"(d[69]), "+f"(d[70]), "+f"(d[71]), "+f"(d[72]), "+f"(d[73]), "+f"(d[74]), "+f"(d[75]), "+f"(d[76]), "+f"(d[77]), "+f"(d[78]), "+f"(d[79]), "+f"(d[80]), "+f"(d[81]), "+f"(d[82]), "+f"(d[83]), "+f"(d[84]), "+f"(d[85]), "+f"(d[86]), "+f"(d[87]), "+f"(d[88]), "+f"(d[89]), "+f"(d[90]), "+f"(d[91]), "+f"(d[92]), "+f"(d[93]), "+f"(d[94]), "+f"(d[95]), "+f"(d[96]), "+f"(d[97]), "+f"(d[98]), "+f"(d[99]), "+f"(d[100]), "+f"(d[101]), "+f"(d[102]), "+f"(d[103]), "+f"(d[104]), "+f"(d[105]), "+f"(d[106]), "+f"(d[107]), "+f"(d[108]), "+f"(d[109]), "+f"(d[110]), "+f"(d[111]), "+f"(d[112]), "+f"(d[113]), "+f"(d[114]), "+f"(d[115]), "+f"(d[116]), "+f"(d[117]), "+f"(d[118]), "+f"(d[119]), "+f"(d[120]), "+f"(d[121]), "+f"(d[122]), "+f"(d[123]), "+f"(d[124]), "+f"(d[125]), "+f"(d[126]), "+f"(d[127])
    : "l"(descA), "l"(descB), "r"(scaleD));
}

__device__ __forceinline__ void wgmma_m64n128k16_ss(float (&d)[64], uint64_t descA, uint64_t descB, int scaleD) {
  asm volatile("{\n.reg .pred p;\n"
    "setp.ne.b32 p, %66, 0;\n"
    "wgmma.mma_async.sync.aligned.m64n128k16.f32.bf16.bf16 "
    "{%0, %1, %2, %3, %4, %5, %6, %7, %8, %9, %10, %11, %12, %13, %14, %15, %16, %17, %18, %19, %20, %21, %22, %23, %24, %25, %26, %27, %28, %29, %30, %31, %32, %33, %34, %35, %36, %37, %38, %39, %40, %41, %42, %43, %44, %45, %46, %47, %48, %49, %50, %51, %52, %53, %54, %55, %56, %57, %58, %59, %60, %61, %62, %63}, "
    "%64, %65, p, 1, 1, 0, 1;\n}\n"
    : "+f"(d[0]), "+f"(d[1]), "+f"(d[2]), "+f"(d[3]), "+f"(d[4]), "+f"(d[5]), "+f"(d[6]), "+f"(d[7]), "+f"(d[8]), "+f"(d[9]), "+f"(d[10]), "+f"(d[11]), "+f"(d[12]), "+f"(d[13]), "+f"(d[14]), "+f"(d[15]), "+f"(d[16]), "+f"(d[17]), "+f"(d[18]), "+f"(d[19]), "+f"(d[20]), "+f"(d[21]), "+f"(d[22]), "+f"(d[23]), "+f"(d[24]), "+f"(d[25]), "+f"(d[26]), "+f"(d[27]), "+f"(d[28]), "+f"(d[29]), "+f"(d[30]), "+f"(d[31]), "+f"(d[32]), "+f"(d[33]), "+f"(d[34]), "+f"(d[35]), "+f"(d[36]), "+f"(d[37]), "+f"(d[38]), "+f"(d[39]), "+f"(d[40]), "+f"(d[41]), "+f"(d[42]), "+f"(d[43]), "+f"(d[44]), "+f"(d[45]), "+f"(d[46]), "+f"(d[47]), "+f"(d[48]), "+f"(d[49]), "+f"(d[50]), "+f"(d[51]), "+f"(d[52]), "+f"(d[53]), "+f"(d[54]), "+f"(d[55]), "+f"(d[56]), "+f"(d[57]), "+f"(d[58]), "+f"(d[59]), "+f"(d[60]), "+f"(d[61]), "+f"(d[62]), "+f"(d[63])
    : "l"(descA), "l"(descB), "r"(scaleD));
}

__device__ __forceinline__ void wgmma_m64n128k16_rs_kmaj(float (&d)[64], uint32_t a0, uint32_t a1, uint32_t a2, uint32_t a3, uint64_t descB, int scaleD) {
  asm volatile("{\n.reg .pred p;\n"
    "setp.ne.b32 p, %69, 0;\n"
    "wgmma.mma_async.sync.aligned.m64n128k16.f32.bf16.bf16 "
    "{%0, %1, %2, %3, %4, %5, %6, %7, %8, %9, %10, %11, %12, %13, %14, %15, %16, %17, %18, %19, %20, %21, %22, %23, %24, %25, %26, %27, %28, %29, %30, %31, %32, %33, %34, %35, %36, %37, %38, %39, %40, %41, %42, %43, %44, %45, %46, %47, %48, %49, %50, %51, %52, %53, %54, %55, %56, %57, %58, %59, %60, %61, %62, %63}, "
    "{%64, %65, %66, %67}, %68, p, 1, 1, 0;\n}\n"
    : "+f"(d[0]), "+f"(d[1]), "+f"(d[2]), "+f"(d[3]), "+f"(d[4]), "+f"(d[5]), "+f"(d[6]), "+f"(d[7]), "+f"(d[8]), "+f"(d[9]), "+f"(d[10]), "+f"(d[11]), "+f"(d[12]), "+f"(d[13]), "+f"(d[14]), "+f"(d[15]), "+f"(d[16]), "+f"(d[17]), "+f"(d[18]), "+f"(d[19]), "+f"(d[20]), "+f"(d[21]), "+f"(d[22]), "+f"(d[23]), "+f"(d[24]), "+f"(d[25]), "+f"(d[26]), "+f"(d[27]), "+f"(d[28]), "+f"(d[29]), "+f"(d[30]), "+f"(d[31]), "+f"(d[32]), "+f"(d[33]), "+f"(d[34]), "+f"(d[35]), "+f"(d[36]), "+f"(d[37]), "+f"(d[38]), "+f"(d[39]), "+f"(d[40]), "+f"(d[41]), "+f"(d[42]), "+f"(d[43]), "+f"(d[44]), "+f"(d[45]), "+f"(d[46]), "+f"(d[47]), "+f"(d[48]), "+f"(d[49]), "+f"(d[50]), "+f"(d[51]), "+f"(d[52]), "+f"(d[53]), "+f"(d[54]), "+f"(d[55]), "+f"(d[56]), "+f"(d[57]), "+f"(d[58]), "+f"(d[59]), "+f"(d[60]), "+f"(d[61]), "+f"(d[62]), "+f"(d[63])
    : "r"(a0), "r"(a1), "r"(a2), "r"(a3), "l"(descB), "r"(scaleD));
}

__device__ __forceinline__ void wgmma_m64n32k16_rs_mnmaj(float (&d)[16], uint32_t a0, uint32_t a1, uint32_t a2, uint32_t a3, uint64_t descB, int scaleD) {
  asm volatile("{\n.reg .pred p;\n"
    "setp.ne.b32 p, %21, 0;\n"
    "wgmma.mma_async.sync.aligned.m64n32k16.f32.bf16.bf16 "
    "{%0, %1, %2, %3, %4, %5, %6, %7, %8, %9, %10, %11, %12, %13, %14, %15}, "
    "{%16, %17, %18, %19}, %20, p, 1, 1, 1;\n}\n"
    : "+f"(d[0]), "+f"(d[1]), "+f"(d[2]), "+f"(d[3]), "+f"(d[4]), "+f"(d[5]), "+f"(d[6]), "+f"(d[7]), "+f"(d[8]), "+f"(d[9]), "+f"(d[10]), "+f"(d[11]), "+f"(d[12]), "+f"(d[13]), "+f"(d[14]), "+f"(d[15])
    : "r"(a0), "r"(a1), "r"(a2), "r"(a3), "l"(descB), "r"(scaleD));
}

__device__ __forceinline__ void wgmma_m64n64k16_rs_kmaj(float (&d)[32], uint32_t a0, uint32_t a1, uint32_t a2, uint32_t a3, uint64_t descB, int scaleD) {
  asm volatile("{\n.reg .pred p;\n"
    "setp.ne.b32 p, %37, 0;\n"
    "wgmma.mma_async.sync.aligned.m64n64k16.f32.bf16.bf16 "
    "{%0, %1, %2, %3, %4, %5, %6, %7, %8, %9, %10, %11, %12, %13, %14, %15, %16, %17, %18, %19, %20, %21, %22, %23, %24, %25, %26, %27, %28, %29, %30, %31}, "
    "{%32, %33, %34, %35}, %36, p, 1, 1, 0;\n}\n"
    : "+f"(d[0]), "+f"(d[1]), "+f"(d[2]), "+f"(d[3]), "+f"(d[4]), "+f"(d[5]), "+f"(d[6]), "+f"(d[7]), "+f"(d[8]), "+f"(d[9]), "+f"(d[10]), "+f"(d[11]), "+f"(d[12]), "+f"(d[13]), "+f"(d[14]), "+f"(d[15]), "+f"(d[16]), "+f"(d[17]), "+f"(d[18]), "+f"(d[19]), "+f"(d[20]), "+f"(d[21]), "+f"(d[22]), "+f"(d[23]), "+f"(d[24]), "+f"(d[25]), "+f"(d[26]), "+f"(d[27]), "+f"(d[28]), "+f"(d[29]), "+f"(d[30]), "+f"(d[31])
    : "r"(a0), "r"(a1), "r"(a2), "r"(a3), "l"(descB), "r"(scaleD));
}

#define TRACE(k) do { } while (0)

__global__ void __launch_bounds__(256) ln_kernel(const bf16* __restrict__ x, bf16* __restrict__ xn) {
  int warp = threadIdx.x >> 5, lane = threadIdx.x & 31;
  int row = blockIdx.x * 8 + warp;
  const uint4* px = reinterpret_cast<const uint4*>(x + (size_t)row * DM);
  float v[32];
#pragma unroll
  for (int i = 0; i < 4; i++) {
    uint4 u = __ldg(px + i * 32 + lane);
    uint32_t w[4] = {u.x, u.y, u.z, u.w};
#pragma unroll
    for (int k = 0; k < 4; k++) {
      v[i * 8 + 2 * k] = __uint_as_float(w[k] << 16);
      v[i * 8 + 2 * k + 1] = __uint_as_float(w[k] & 0xffff0000u);
    }
  }
  float s = 0.f;
#pragma unroll
  for (int i = 0; i < 32; i++) s += v[i];
#pragma unroll
  for (int o = 16; o > 0; o >>= 1) s += __shfl_xor_sync(0xffffffffu, s, o);
  float mean = s * (1.0f / DM);
  float q = 0.f;
#pragma unroll
  for (int i = 0; i < 32; i++) {
    float d = v[i] - mean;
    q = fmaf(d, d, q);
  }
#pragma unroll
  for (int o = 16; o > 0; o >>= 1) q += __shfl_xor_sync(0xffffffffu, q, o);
  float rstd = rsqrtf(q * (1.0f / DM) + 1e-5f);
  uint4* po = reinterpret_cast<uint4*>(xn + (size_t)row * DM);
#pragma unroll
  for (int i = 0; i < 4; i++) {
    uint4 u;
    u.x = pack_bf16((v[i * 8 + 0] - mean) * rstd, (v[i * 8 + 1] - mean) * rstd);
    u.y = pack_bf16((v[i * 8 + 2] - mean) * rstd, (v[i * 8 + 3] - mean) * rstd);
    u.z = pack_bf16((v[i * 8 + 4] - mean) * rstd, (v[i * 8 + 5] - mean) * rstd);
    u.w = pack_bf16((v[i * 8 + 6] - mean) * rstd, (v[i * 8 + 7] - mean) * rstd);
    po[i * 32 + lane] = u;
  }
}

constexpr int G1_STAGES = 4;
constexpr int G1_A_BYTES = 128 * 64 * 2;
constexpr int G1_B_BYTES = 64 * 256 * 2;
constexpr int G1_STAGE_BYTES = G1_A_BYTES + G1_B_BYTES;
constexpr int G1_STG_BYTES = 64 * 128 * 2;
constexpr int G1_SMEM = G1_STAGES * G1_STAGE_BYTES + 2 * G1_STG_BYTES + 1024   + 256  ;
constexpr int G1_NTILES_QKV = 12;
constexpr int G1_NTILES_FFN = 28;

template <int CL>
__global__ void __launch_bounds__(384, 1)
    gemm1_kernel(const __grid_constant__ CUtensorMap mapA, const __grid_constant__ CUtensorMap mapWqkv,
                 const __grid_constant__ CUtensorMap mapWg, const __grid_constant__ CUtensorMap mapWu,
                 const __grid_constant__ CUtensorMap mapQo, const __grid_constant__ CUtensorMap mapHo) {
  extern __shared__ uint8_t smem_raw[];
  uint32_t sbase = (smem_u32(smem_raw) + 1023u) & ~1023u;
  uint32_t stg_base = sbase + G1_STAGES * G1_STAGE_BYTES;
  uint32_t bar_base = stg_base + 2 * G1_STG_BYTES;
  const int wg = threadIdx.x >> 7;
  const int warp = threadIdx.x >> 5, lane = threadIdx.x & 31;
  const uint32_t cta_rank = (CL > 1) ? cluster_ctarank() : 0;
  const int cluster_id = blockIdx.x / CL;
  const int n_clusters = gridDim.x / CL;
  constexpr int MG = 16 / CL;
  constexpr int N_CT = (G1_NTILES_QKV + G1_NTILES_FFN) * MG;

  if (threadIdx.x == 0) {
    for (int s = 0; s < G1_STAGES; s++) {
      mbar_init(bar_base + 8 * s, 1);
      mbar_init(bar_base + 64 + 8 * s, CL);
      mbar_init(bar_base + 128 + 8 * s, 8);
    }
    fence_barrier_init();
  }
  __syncthreads();
  if (CL > 1) cluster_sync_all();

  if (wg == 0) {
    reg_dealloc<40>();
    if (warp == 0 && lane == 0) {
      prefetch_tmap(&mapA); prefetch_tmap(&mapWqkv); prefetch_tmap(&mapWg); prefetch_tmap(&mapWu);
      int stage = 0, phase = 0;
      for (int ct = cluster_id; ct < N_CT; ct += n_clusters) {
        int n_blk = ct / MG;
        int m_blk = (ct % MG) * CL + cta_rank;
        bool ffn = n_blk >= G1_NTILES_QKV;
        for (int kb = 0; kb < 16; kb++) {
          uint32_t full = bar_base + 8 * stage, empty = bar_base + 64 + 8 * stage;
          mbar_wait(empty, phase ^ 1);
          mbar_expect_tx(full, G1_STAGE_BYTES);
          uint32_t sa = sbase + stage * G1_STAGE_BYTES;
          uint32_t sb = sa + G1_A_BYTES;
          tma_load_2d(sa, &mapA, full, kb * 64, m_blk * 128);
#pragma unroll
          for (int i = 0; i < 4 / CL; i++) {
            int bi = cta_rank * (4 / CL) + i;
            const CUtensorMap* mp;
            int col;
            if (!ffn) { mp = &mapWqkv; col = n_blk * 256 + bi * 64; }
            else { mp = (bi < 2) ? &mapWg : &mapWu; col = (n_blk - G1_NTILES_QKV) * 128 + (bi & 1) * 64; }
            if (CL > 1) tma_load_2d_mc(sb + bi * 8192, mp, full, col, kb * 64, (uint16_t)((1 << CL) - 1));
            else tma_load_2d(sb + bi * 8192, mp, full, col, kb * 64);
          }
          if (++stage == G1_STAGES) { stage = 0; phase ^= 1; }
        }
      }
    } else if (warp == 1 && lane == 0) {
      int stage = 0, phase = 0;
      for (int ct = cluster_id; ct < N_CT; ct += n_clusters) {
        for (int kb = 0; kb < 16; kb++) {
          mbar_wait(bar_base + 128 + 8 * stage, phase);
          if (CL > 1) {
#pragma unroll
            for (int c = 0; c < CL; c++) mbar_arrive_cluster(bar_base + 64 + 8 * stage, c);
          } else {
            mbar_arrive(bar_base + 64 + 8 * stage);
          }
          if (++stage == G1_STAGES) { stage = 0; phase ^= 1; }
        }
      }
    }
  } else {
    reg_alloc<232>();
    const int cw = wg - 1;
    const int wq = warp & 3;
    const bool elected = (threadIdx.x & 127) == 0;
    int stage = 0, phase = 0;
    float acc[128];
    const uint32_t stg = stg_base + cw * G1_STG_BYTES;
    const int st_row = wq * 16 + ((lane >> 3) & 1) * 8 + (lane & 7);
    const uint32_t st_addr = stg + st_row * 128;
    const uint32_t st_xor = (uint32_t)(lane & 7);
    const int st_hi = lane >> 4;
    for (int ct = cluster_id; ct < N_CT; ct += n_clusters) {
      int n_blk = ct / MG;
      int m_blk = (ct % MG) * CL + cta_rank;
      bool ffn = n_blk >= G1_NTILES_QKV;
      int prev_stage = 0;
      for (int kb = 0; kb < 16; kb++) {
        uint32_t full = bar_base + 8 * stage;
        mbar_wait(full, phase);
        uint32_t sa = sbase + stage * G1_STAGE_BYTES;
        uint64_t descA = make_desc(sa + cw * 8192, 16, 1024, 1);
        uint64_t descB = make_desc(sa + G1_A_BYTES, 8192, 1024, 1);
        wgmma_fence();
#pragma unroll
        for (int k = 0; k < 4; k++) {
          wgmma_m64n256k16_ss(acc, descA + (uint64_t)(k * 2), descB + (uint64_t)(k * 128), (kb | k) != 0);
        }
        wgmma_commit();
        if (kb > 0) {
          wgmma_wait<1>();
          if (lane == 0) mbar_arrive(bar_base + 128 + 8 * prev_stage);
        }
        prev_stage = stage;
        if (++stage == G1_STAGES) { stage = 0; phase ^= 1; }
      }
      wgmma_wait<0>();
      if (lane == 0) mbar_arrive(bar_base + 128 + 8 * prev_stage);
      const int row0 = m_blk * 128 + cw * 64;
      if (!ffn) {
#pragma unroll
        for (int pass = 0; pass < 2; pass++) {
          if (elected) bulk_wait_read0();
          named_bar(1 + cw, 128);
#pragma unroll
          for (int jj = 0; jj < 8; jj++) {
            int j = pass * 16 + jj * 2;
            int cb = jj * 2 + st_hi;
            uint32_t addr = st_addr + (cb >> 3) * 8192 + ((((uint32_t)cb & 7u) ^ st_xor) << 4);
            stmatrix_x4(addr, pack_bf16(acc[4 * j], acc[4 * j + 1]), pack_bf16(acc[4 * j + 2], acc[4 * j + 3]),
                        pack_bf16(acc[4 * j + 4], acc[4 * j + 5]), pack_bf16(acc[4 * j + 6], acc[4 * j + 7]));
          }
          fence_proxy_async();
          named_bar(1 + cw, 128);
          if (elected) {
            tma_store_2d(&mapQo, stg, n_blk * 256 + pass * 128, row0);
            tma_store_2d(&mapQo, stg + 8192, n_blk * 256 + pass * 128 + 64, row0);
            bulk_commit();
          }
        }
      } else {
        if (elected) bulk_wait_read0();
        named_bar(1 + cw, 128);
#pragma unroll
        for (int jj = 0; jj < 8; jj++) {
          int j = jj * 2;
          uint32_t r[4];
#pragma unroll
          for (int t = 0; t < 4; t++) {
            float h0 = gelu_tanh(acc[4 * j + 2 * t]) * acc[64 + 4 * j + 2 * t];
            float h1 = gelu_tanh(acc[4 * j + 2 * t + 1]) * acc[64 + 4 * j + 2 * t + 1];
            r[t] = pack_bf16(h0, h1);
          }
          int cb = jj * 2 + st_hi;
          uint32_t addr = st_addr + (cb >> 3) * 8192 + ((((uint32_t)cb & 7u) ^ st_xor) << 4);
          stmatrix_x4(addr, r[0], r[1], r[2], r[3]);
        }
        fence_proxy_async();
        named_bar(1 + cw, 128);
        if (elected) {
          tma_store_2d(&mapHo, stg, (n_blk - G1_NTILES_QKV) * 128, row0);
          tma_store_2d(&mapHo, stg + 8192, (n_blk - G1_NTILES_QKV) * 128 + 64, row0);
          bulk_commit();
        }
      }
    }
    if (elected) bulk_wait0();
  }
  if (CL > 1) { asm volatile("barrier.cluster.arrive.release;\nbarrier.cluster.wait.acquire;" ::: "memory"); }
}

constexpr int AT_STAGES = 4;
constexpr int AT_TILE_BYTES = 128 * 64;
constexpr int AT_SMEM = AT_STAGES * 2 * AT_TILE_BYTES + 1024 + 256;
constexpr int AT_THREADS = 512;

__global__ void __launch_bounds__(AT_THREADS, 1)
    attn_kernel(const __grid_constant__ CUtensorMap mapKV, const bf16* __restrict__ qkv, bf16* __restrict__ o) {
  extern __shared__ uint8_t smem_raw[];
  uint32_t sbase = (smem_u32(smem_raw) + 1023u) & ~1023u;
  uint32_t bar_base = sbase + AT_STAGES * 2 * AT_TILE_BYTES;
  const int warp = threadIdx.x >> 5, lane = threadIdx.x & 31;
  const int head = blockIdx.x >> 3, qblk = blockIdx.x & 7;
  if (threadIdx.x == 0) {
    for (int s = 0; s < AT_STAGES; s++) {
      mbar_init(bar_base + 8 * s, 1);
      mbar_init(bar_base + 64 + 8 * s, 1);
      mbar_init(bar_base + 128 + 8 * s, 16);
    }
    fence_barrier_init();
  }
  __syncthreads();
  constexpr int NT = SEQ / 128;

  constexpr int LA = 2;
  auto issue_tile = [&](int jn) {
    int s = jn & (AT_STAGES - 1), ph = (jn / AT_STAGES) & 1;
    mbar_wait(bar_base + 128 + 8 * s, ph ^ 1);
    uint32_t sk = sbase + s * 2 * AT_TILE_BYTES;
    mbar_expect_tx(bar_base + 8 * s, AT_TILE_BYTES);
    tma_load_2d(sk, &mapKV, bar_base + 8 * s, DM + head * DH, jn * 128);
    mbar_expect_tx(bar_base + 64 + 8 * s, AT_TILE_BYTES);
    tma_load_2d(sk + AT_TILE_BYTES, &mapKV, bar_base + 64 + 8 * s, 2 * DM + head * DH, jn * 128);
  };
  if (threadIdx.x == 0) {
    prefetch_tmap(&mapKV);
    for (int jn = 0; jn < LA; jn++) issue_tile(jn);
  }

  const int wg = warp >> 2, wq = warp & 3, g = lane >> 2, q = lane & 3;
  const int row0 = qblk * 256 + wg * 64 + wq * 16 + g;
  uint32_t qf[2][4];
  {
    const bf16* qp = qkv + (size_t)row0 * (3 * DM) + head * DH + 2 * q;
#pragma unroll
    for (int kk = 0; kk < 2; kk++) {
      qf[kk][0] = *reinterpret_cast<const uint32_t*>(qp + kk * 16);
      qf[kk][1] = *reinterpret_cast<const uint32_t*>(qp + 8 * 3 * DM + kk * 16);
      qf[kk][2] = *reinterpret_cast<const uint32_t*>(qp + kk * 16 + 8);
      qf[kk][3] = *reinterpret_cast<const uint32_t*>(qp + 8 * 3 * DM + kk * 16 + 8);
    }
  }
  const float sl2 = 0.17677669529663687f * 1.4426950408889634f;
  float oacc[16];
#pragma unroll
  for (int i = 0; i < 16; i++) oacc[i] = 0.f;
  float m0 = -INFINITY, m1 = -INFINITY, l0 = 0.f, l1 = 0.f;
  constexpr int NU = 2 * NT;
  float sc[32];
  uint32_t pf[16];

  auto issue_qk = [&](int u) {
    int t = u >> 1, s = t & (AT_STAGES - 1);
    uint64_t descK = make_desc(sbase + s * 2 * AT_TILE_BYTES + (u & 1) * 4096, 16, 512, 2);
    wgmma_m64n64k16_rs_kmaj(sc, qf[0][0], qf[0][1], qf[0][2], qf[0][3], descK, 0);
    wgmma_m64n64k16_rs_kmaj(sc, qf[1][0], qf[1][1], qf[1][2], qf[1][3], descK + 2, 1);
    wgmma_commit();
  };
  auto wait_k = [&](int u) {
    if ((u & 1) == 0) {
      int t = u >> 1, s = t & (AT_STAGES - 1);
      if (threadIdx.x == 0 && t + LA < NT) issue_tile(t + LA);
      __syncwarp();
      mbar_wait(bar_base + 8 * s, (t / AT_STAGES) & 1);
    }
  };
  auto softmax_step = [&](float& a0, float& a1) {
    float mx0 = fmaxf(sc[0], sc[1]), mx1 = fmaxf(sc[2], sc[3]);
#pragma unroll
    for (int i = 1; i < 8; i++) {
      mx0 = fmaxf(mx0, fmaxf(sc[4 * i], sc[4 * i + 1]));
      mx1 = fmaxf(mx1, fmaxf(sc[4 * i + 2], sc[4 * i + 3]));
    }
    mx0 = fmaxf(mx0, __shfl_xor_sync(0xffffffffu, mx0, 1));
    mx1 = fmaxf(mx1, __shfl_xor_sync(0xffffffffu, mx1, 1));
    mx0 = fmaxf(mx0, __shfl_xor_sync(0xffffffffu, mx0, 2));
    mx1 = fmaxf(mx1, __shfl_xor_sync(0xffffffffu, mx1, 2));
    float mn0 = fmaxf(m0, mx0), mn1 = fmaxf(m1, mx1);
    a0 = ex2((m0 - mn0) * sl2); a1 = ex2((m1 - mn1) * sl2);
    m0 = mn0; m1 = mn1;
    float nb0 = -mn0 * sl2, nb1 = -mn1 * sl2;
    float s0 = 0.f, s1 = 0.f;
#pragma unroll
    for (int i = 0; i < 8; i++) {
      sc[4 * i] = ex2(fmaf(sc[4 * i], sl2, nb0));
      sc[4 * i + 1] = ex2(fmaf(sc[4 * i + 1], sl2, nb0));
      sc[4 * i + 2] = ex2(fmaf(sc[4 * i + 2], sl2, nb1));
      sc[4 * i + 3] = ex2(fmaf(sc[4 * i + 3], sl2, nb1));
      s0 += sc[4 * i] + sc[4 * i + 1];
      s1 += sc[4 * i + 2] + sc[4 * i + 3];
    }
    l0 = fmaf(l0, a0, s0);
    l1 = fmaf(l1, a1, s1);
  };
  auto convert_p = [&]() {
#pragma unroll
    for (int i = 0; i < 8; i++) {
      pf[2 * i] = pack_bf16(sc[4 * i], sc[4 * i + 1]);
      pf[2 * i + 1] = pack_bf16(sc[4 * i + 2], sc[4 * i + 3]);
    }
  };

  wait_k(0);
  wgmma_fence();
  issue_qk(0);
  wgmma_wait<0>();
#pragma unroll
  for (int i = 0; i < 32; i++) asm volatile("" : "+f"(sc[i])::"memory");
  {
    float a0, a1;
    softmax_step(a0, a1);
    convert_p();
  }
  auto issue_pv = [&](int u) {
    int t = u >> 1, s = t & (AT_STAGES - 1);
    uint64_t descV = make_desc(sbase + s * 2 * AT_TILE_BYTES + AT_TILE_BYTES + (u & 1) * 4096, 16, 512, 2);
#pragma unroll
    for (int kk = 0; kk < 4; kk++) {
      wgmma_m64n32k16_rs_mnmaj(oacc, pf[4 * kk], pf[4 * kk + 1], pf[4 * kk + 2], pf[4 * kk + 3], descV + (uint64_t)(kk * 64), 1);
    }
    wgmma_commit();
  };
  auto wait_v = [&](int u) {
    int t = u >> 1, s = t & (AT_STAGES - 1);
    if ((u & 1) == 0) mbar_wait(bar_base + 64 + 8 * s, (t / AT_STAGES) & 1);
  };
#pragma unroll 1
  for (int u = 0; u < NU - 1; u++) {
    TRACE(0);
    wait_k(u + 1);
    wait_v(u);
    TRACE(1);
    wgmma_fence();
    TRACE(6);
    issue_qk(u + 1);
    TRACE(7);
    issue_pv(u);
    TRACE(2);
    wgmma_wait<1>();
#pragma unroll
    for (int i = 0; i < 32; i++) asm volatile("" : "+f"(sc[i])::"memory");
    TRACE(3);
    float a0, a1;
    softmax_step(a0, a1);
    TRACE(4);
    wgmma_wait<0>();
    TRACE(5);
#pragma unroll
    for (int i = 0; i < 16; i++) asm volatile("" : "+f"(oacc[i])::"memory");
    if ((u & 1) == 1 && lane == 0) mbar_arrive(bar_base + 128 + 8 * ((u >> 1) & (AT_STAGES - 1)));
    convert_p();
#pragma unroll
    for (int i = 0; i < 4; i++) {
      oacc[4 * i] *= a0; oacc[4 * i + 1] *= a0; oacc[4 * i + 2] *= a1; oacc[4 * i + 3] *= a1;
    }
  }
  wgmma_fence();
  issue_pv(NU - 1);
  wgmma_wait<0>();
#pragma unroll
  for (int i = 0; i < 16; i++) asm volatile("" : "+f"(oacc[i])::"memory");
  l0 += __shfl_xor_sync(0xffffffffu, l0, 1);
  l1 += __shfl_xor_sync(0xffffffffu, l1, 1);
  l0 += __shfl_xor_sync(0xffffffffu, l0, 2);
  l1 += __shfl_xor_sync(0xffffffffu, l1, 2);
  float inv0 = 1.0f / l0, inv1 = 1.0f / l1;
  bf16* op = o + (size_t)row0 * DM + head * DH + 2 * q;
#pragma unroll
  for (int i = 0; i < 4; i++) {
    *reinterpret_cast<uint32_t*>(op + 8 * i) = pack_bf16(oacc[4 * i] * inv0, oacc[4 * i + 1] * inv0);
    *reinterpret_cast<uint32_t*>(op + 8 * DM + 8 * i) = pack_bf16(oacc[4 * i + 2] * inv1, oacc[4 * i + 3] * inv1);
  }
}

constexpr int G2_STAGES = 6;
constexpr int G2_A_BYTES = 128 * 64 * 2;
constexpr int G2_B_BYTES = 64 * 128 * 2;
constexpr int G2_STAGE_BYTES = G2_A_BYTES + G2_B_BYTES;
constexpr int G2_X_BYTES = 128 * 128 * 2;
constexpr int G2_SMEM = G2_STAGES * G2_STAGE_BYTES + G2_X_BYTES + 1024 + 256;
constexpr int G2_KB1 = FF / 64;
constexpr int G2_KB2 = DM / 64;

template <int CL>
__global__ void __launch_bounds__(384, 1)
    gemm2_kernel(const __grid_constant__ CUtensorMap mapH, const __grid_constant__ CUtensorMap mapWd,
                 const __grid_constant__ CUtensorMap mapO, const __grid_constant__ CUtensorMap mapWo,
                 const __grid_constant__ CUtensorMap mapX, const __grid_constant__ CUtensorMap mapOut) {
  extern __shared__ uint8_t smem_raw[];
  uint32_t sbase = (smem_u32(smem_raw) + 1023u) & ~1023u;
  uint32_t xt_base = sbase + G2_STAGES * G2_STAGE_BYTES;
  uint32_t bar_base = xt_base + G2_X_BYTES;
  const int wg = threadIdx.x >> 7;
  const int warp = threadIdx.x >> 5, lane = threadIdx.x & 31;
  const uint32_t cta_rank = (CL > 1) ? cluster_ctarank() : 0;
  const int cluster_id = blockIdx.x / CL;
  const int mi = cta_rank;
  const int m_blk = (cluster_id & 7) * 2 + mi;
  const int n_blk = cluster_id >> 3;

  if (threadIdx.x == 0) {
    for (int s = 0; s < G2_STAGES; s++) {
      mbar_init(bar_base + 8 * s, 1);
      mbar_init(bar_base + 64 + 8 * s, 2);
      mbar_init(bar_base + 128 + 8 * s, 8);
    }
    mbar_init(bar_base + 192, 1);
    fence_barrier_init();
  }
  __syncthreads();
  if (CL > 1) cluster_sync_all();

  if (wg == 0) {
    reg_dealloc<40>();
    if (warp == 0 && lane == 0) {
      prefetch_tmap(&mapH); prefetch_tmap(&mapWd); prefetch_tmap(&mapO); prefetch_tmap(&mapWo);
      mbar_expect_tx(bar_base + 192, G2_X_BYTES);
      tma_load_2d(xt_base, &mapX, bar_base + 192, n_blk * 128, m_blk * 128);
      tma_load_2d(xt_base + 16384, &mapX, bar_base + 192, n_blk * 128 + 64, m_blk * 128);
      int stage = 0, phase = 0;
      for (int kb = 0; kb < G2_KB1 + G2_KB2; kb++) {
        uint32_t full = bar_base + 8 * stage, empty = bar_base + 64 + 8 * stage;
        mbar_wait(empty, phase ^ 1);
        mbar_expect_tx(full, G2_STAGE_BYTES);
        uint32_t sa = sbase + stage * G2_STAGE_BYTES;
        uint32_t sb = sa + G2_A_BYTES;
        bool first = kb < G2_KB1;
        const CUtensorMap* ma = first ? &mapH : &mapO;
        const CUtensorMap* mb = first ? &mapWd : &mapWo;
        int k0 = (first ? kb : kb - G2_KB1) * 64;
        tma_load_2d(sa, ma, full, k0, m_blk * 128);
#pragma unroll
        for (int i = 0; i < 2; i++) {
          uint32_t dst = sb + i * 8192 + mi * 4096;
          tma_load_2d_mc(dst, mb, full, n_blk * 128 + i * 64, k0 + mi * 32, (uint16_t)3);
        }
        if (++stage == G2_STAGES) { stage = 0; phase ^= 1; }
      }
    } else if (warp == 1 && lane == 0) {
      int stage = 0, phase = 0;
      for (int kb = 0; kb < G2_KB1 + G2_KB2 - 1; kb++) {
        mbar_wait(bar_base + 128 + 8 * stage, phase);
        mbar_arrive_cluster(bar_base + 64 + 8 * stage, 0);
        mbar_arrive_cluster(bar_base + 64 + 8 * stage, 1);
        if (++stage == G2_STAGES) { stage = 0; phase ^= 1; }
      }
    }
  } else {
    reg_alloc<232>();
    const int cw = wg - 1;
    const int wq = warp & 3, g = lane >> 2, q = lane & 3;
    int stage = 0, phase = 0, prev_stage = 0;
    float accf[64], accs[64];
    for (int kb = 0; kb < G2_KB1; kb++) {
      mbar_wait(bar_base + 8 * stage, phase);
      uint32_t sa = sbase + stage * G2_STAGE_BYTES;
      uint64_t descA = make_desc(sa + cw * 8192, 16, 1024, 1);
      uint64_t descB = make_desc(sa + G2_A_BYTES, 8192, 1024, 1);
      wgmma_fence();
#pragma unroll
      for (int k = 0; k < 4; k++) wgmma_m64n128k16_ss(accf, descA + (uint64_t)(k * 2), descB + (uint64_t)(k * 128), (kb | k) != 0);
      wgmma_commit();
      if (kb > 0) {
        wgmma_wait<1>();
        uint32_t empty = bar_base + 64 + 8 * prev_stage;
        if (lane == 0) mbar_arrive(empty + 64);
      }
      prev_stage = stage;
      if (++stage == G2_STAGES) { stage = 0; phase ^= 1; }
    }
    for (int kb = 0; kb < G2_KB2; kb++) {
      mbar_wait(bar_base + 8 * stage, phase);
      uint32_t sa = sbase + stage * G2_STAGE_BYTES;
      uint64_t descA = make_desc(sa + cw * 8192, 16, 1024, 1);
      uint64_t descB = make_desc(sa + G2_A_BYTES, 8192, 1024, 1);
      wgmma_fence();
#pragma unroll
      for (int k = 0; k < 4; k++) wgmma_m64n128k16_ss(accs, descA + (uint64_t)(k * 2), descB + (uint64_t)(k * 128), (kb | k) != 0);
      wgmma_commit();
      wgmma_wait<1>();
      {
        uint32_t empty = bar_base + 64 + 8 * prev_stage;
        if (lane == 0) mbar_arrive(empty + 64);
      }
      prev_stage = stage;
      if (++stage == G2_STAGES) { stage = 0; phase ^= 1; }
    }
    wgmma_wait<0>();
    mbar_wait(bar_base + 192, 0);
    {
      const int st_row = cw * 64 + wq * 16 + ((lane >> 3) & 1) * 8 + (lane & 7);
      const uint32_t st_addr = xt_base + st_row * 128;
      const uint32_t st_xor = (uint32_t)(lane & 7);
      const int st_hi = lane >> 4;
#pragma unroll
      for (int jj = 0; jj < 8; jj++) {
        int cb = jj * 2 + st_hi;
        uint32_t addr = st_addr + (cb >> 3) * 16384 + ((((uint32_t)cb & 7u) ^ st_xor) << 4);
        uint32_t xv[4], r[4];
        asm volatile("ldmatrix.sync.aligned.m8n8.x4.shared.b16 {%0, %1, %2, %3}, [%4];"
                     : "=r"(xv[0]), "=r"(xv[1]), "=r"(xv[2]), "=r"(xv[3]) : "r"(addr) : "memory");
#pragma unroll
        for (int t = 0; t < 4; t++) {
          float x0 = __uint_as_float(xv[t] << 16), x1 = __uint_as_float(xv[t] & 0xffff0000u);
          float f0 = accf[8 * jj + 2 * t], f1 = accf[8 * jj + 2 * t + 1];
          float s0 = accs[8 * jj + 2 * t], s1 = accs[8 * jj + 2 * t + 1];
          float g0 = __fdividef(f0, 1.0f + __expf(-f0));
          float g1 = __fdividef(f1, 1.0f + __expf(-f1));
          r[t] = pack_bf16(fmaf(s0, g0, x0), fmaf(s1, g1, x1));
        }
        stmatrix_x4(addr, r[0], r[1], r[2], r[3]);
      }
      fence_proxy_async();
      named_bar(1 + cw, 128);
      if ((threadIdx.x & 127) == 0) {
        tma_store_2d(&mapOut, xt_base + cw * 8192, n_blk * 128, m_blk * 128 + cw * 64);
        tma_store_2d(&mapOut, xt_base + 16384 + cw * 8192, n_blk * 128 + 64, m_blk * 128 + cw * 64);
        bulk_commit();
        bulk_wait0();
      }
    }
  }
  if (CL > 1) { asm volatile("barrier.cluster.arrive.release;\nbarrier.cluster.wait.acquire;" ::: "memory"); }
}

typedef CUresult (*PFN_encodeTiled)(CUtensorMap*, CUtensorMapDataType, cuuint32_t, void*, const cuuint64_t*, const cuuint64_t*,
                                    const cuuint32_t*, const cuuint32_t*, CUtensorMapInterleave, CUtensorMapSwizzle,
                                    CUtensorMapL2promotion, CUtensorMapFloatOOBfill);

CUtensorMap make_map(PFN_encodeTiled f, const void* ptr, uint64_t inner, uint64_t outer, uint32_t box_inner, uint32_t box_outer,
                     CUtensorMapSwizzle sw) {
  CUtensorMap m;
  cuuint64_t dims[2] = {inner, outer};
  cuuint64_t strides[1] = {inner * 2};
  cuuint32_t box[2] = {box_inner, box_outer};
  cuuint32_t es[2] = {1, 1};
  f(&m, CU_TENSOR_MAP_DATA_TYPE_BFLOAT16, 2, const_cast<void*>(ptr), dims, strides, box, es, CU_TENSOR_MAP_INTERLEAVE_NONE, sw,
    CU_TENSOR_MAP_L2_PROMOTION_L2_256B, CU_TENSOR_MAP_FLOAT_OOB_FILL_NONE);
  return m;
}

template <typename... Args>
void launch_ex(void (*kern)(Args...), int grid, int block, size_t smem, int cluster, Args... args) {
  cudaLaunchConfig_t cfg = {};
  cfg.gridDim = dim3(grid);
  cfg.blockDim = dim3(block);
  cfg.dynamicSmemBytes = smem;
  cfg.stream = cudaStreamPerThread;
  cudaLaunchAttribute attr[1];
  attr[0].id = cudaLaunchAttributeClusterDimension;
  attr[0].val.clusterDim.x = cluster;
  attr[0].val.clusterDim.y = 1;
  attr[0].val.clusterDim.z = 1;
  cfg.attrs = attr;
  cfg.numAttrs = (cluster > 1) ? 1 : 0;
  cudaLaunchKernelEx(&cfg, kern, args...);
}

constexpr int G1_CL = 2;
constexpr int G2_CL = 2;

}

extern "C" void kernel_launch(void* const* d_in, const int* in_sizes, int n_in, void* d_out, int out_size) {
  const bf16* x = (const bf16*)d_in[0];
  const bf16* wqkv = (const bf16*)d_in[1];
  const bf16* wo = (const bf16*)d_in[2];
  const bf16* wg = (const bf16*)d_in[4];
  const bf16* wu = (const bf16*)d_in[5];
  const bf16* wd = (const bf16*)d_in[6];
  bf16* out = (bf16*)d_out;

  static PFN_encodeTiled enc = nullptr;
  static bf16 *p_xn, *p_qkv, *p_h, *p_o;
  if (!enc) {
    void* fn = nullptr;
    cudaDriverEntryPointQueryResult qres;
    cudaGetDriverEntryPoint("cuTensorMapEncodeTiled", &fn, cudaEnableDefault, &qres);
    enc = (PFN_encodeTiled)fn;
    cudaGetSymbolAddress((void**)&p_xn, g_xn);
    cudaGetSymbolAddress((void**)&p_qkv, g_qkv);
    cudaGetSymbolAddress((void**)&p_h, g_h);
    cudaGetSymbolAddress((void**)&p_o, g_o);
    cudaFuncSetAttribute(gemm1_kernel<G1_CL>, cudaFuncAttributeMaxDynamicSharedMemorySize, G1_SMEM);
    cudaFuncSetAttribute(gemm2_kernel<G2_CL>, cudaFuncAttributeMaxDynamicSharedMemorySize, G2_SMEM);
    cudaFuncSetAttribute(attn_kernel, cudaFuncAttributeMaxDynamicSharedMemorySize, AT_SMEM);
  }
  const CUtensorMapSwizzle SW128 = CU_TENSOR_MAP_SWIZZLE_128B, SW64 = CU_TENSOR_MAP_SWIZZLE_64B;
  CUtensorMap mXn = make_map(enc, p_xn, DM, SEQ, 64, 128, SW128);
  CUtensorMap mWqkv = make_map(enc, wqkv, 3 * DM, DM, 64, 64, SW128);
  CUtensorMap mWg = make_map(enc, wg, FF, DM, 64, 64, SW128);
  CUtensorMap mWu = make_map(enc, wu, FF, DM, 64, 64, SW128);
  CUtensorMap mQo = make_map(enc, p_qkv, 3 * DM, SEQ, 64, 64, SW128);
  CUtensorMap mHo = make_map(enc, p_h, FF, SEQ, 64, 64, SW128);
  CUtensorMap mKV = make_map(enc, p_qkv, 3 * DM, SEQ, 32, 128, SW64);
  CUtensorMap mH = make_map(enc, p_h, FF, SEQ, 64, 128, SW128);
  CUtensorMap mWd = make_map(enc, wd, DM, FF, 64, 32, SW128);
  CUtensorMap mO = make_map(enc, p_o, DM, SEQ, 64, 128, SW128);
  CUtensorMap mWo = make_map(enc, wo, DM, DM, 64, 32, SW128);
  CUtensorMap mX = make_map(enc, x, DM, SEQ, 64, 128, SW128);
  CUtensorMap mOut = make_map(enc, out, DM, SEQ, 64, 64, SW128);

  ln_kernel<<<SEQ / 8, 256, 0, cudaStreamPerThread>>>(x, p_xn);
  launch_ex(gemm1_kernel<G1_CL>, (G1_CL == 4) ? 128 : 132, 384, G1_SMEM, G1_CL, mXn, mWqkv, mWg, mWu, mQo, mHo);
  launch_ex(attn_kernel, 256, AT_THREADS, AT_SMEM, 1, mKV, (const bf16*)p_qkv, p_o);
  launch_ex(gemm2_kernel<G2_CL>, 128, 384, G2_SMEM, G2_CL, mH, mWd, mO, mWo, mX, mOut);
}
```
